```python
import torch

def _softmax(x, axis=-1):
    return torch.softmax(x, dim=axis)
def _gelu(x):
    return torch.nn.functional.gelu(x, approximate="tanh")
def _silu(x):
    return torch.nn.functional.silu(x)
def _sigmoid(x):
    return torch.sigmoid(x)
def _layernorm(x, axis=-1, eps=1e-5):
    m = x.mean(dim=axis, keepdim=True)
    v = x.var(dim=axis, keepdim=True, unbiased=False)
    return (x - m) / torch.sqrt(v + eps)
def _scatter_add(tgt, idx, src, axis=0):
    return tgt.clone().index_add_(axis, idx, src)
def _segment_sum(src, seg, n):
    out = torch.zeros((n,) + src.shape[1:], dtype=src.dtype)
    return out.index_add_(0, seg, src)
def _pad(x, pw):
    flat = tuple(v for pair in reversed(pw) for v in pair)
    return torch.nn.functional.pad(x, flat)

kernel_name = 'concat_heads__gqa_block_cached__compressed_kv_cla__decode'

def setup_inputs():

    _w = (lambda a: (lambda t: t.to(torch.bfloat16) if t.is_floating_point() else t)(torch.as_tensor(a)))
    def _A_setup():
        B, Sq, D = 2, 1, 512
        Hq, Hkv, Sk, Dh = 32, 32, 8192, 128
        assert Hq % Hkv == 0, (Hq, Hkv)
        return {
            "x": _w((lambda *s: torch.randn(*s, dtype=torch.bfloat16) * 1.6)(B, Sq, D)),
            "k_cache": _w((lambda *s: torch.randn(*s, dtype=torch.bfloat16) * 1.6)(B, Hkv, Sk, Dh)),
            "v_cache": _w((lambda *s: torch.randn(*s, dtype=torch.bfloat16) * 0.05)(B, Hkv, Sk, Dh)),
            "wq": _w((lambda *s: torch.randn(*s, dtype=torch.bfloat16) * 1.6)(D, Hq * Dh) * (D ** -0.5)),
            "wo": _w((lambda *s: torch.randn(*s, dtype=torch.bfloat16) * 0.05)(Hq * Dh, D) * ((Hq * Dh) ** -0.5)),
        }
    _A_in = _A_setup()

    def _B_setup():
        B, H, Sq, Sk, D, M = 2, 32, 1, 8192, 128, 512
        Dc = 4 * D
        return {
            "x": _w((lambda *s: torch.randn(*s, dtype=torch.bfloat16) * 3.2)(B, Sq, M)),
            "c_kv": _w((lambda *s: torch.randn(*s, dtype=torch.bfloat16) * 0.1)(B, Sk, Dc)),
            "w_q": _w((lambda *s: torch.randn(*s, dtype=torch.bfloat16) * 6.4)(M, H, D) * (M ** -0.5)),
            "w_uk": _w((lambda *s: torch.randn(*s, dtype=torch.bfloat16) * 6.4)(Dc, H, D) * (Dc ** -0.5)),
            "w_uv": _w((lambda *s: torch.randn(*s, dtype=torch.bfloat16) * 0.1)(Dc, H, D) * (Dc ** -0.5)),
            "w_o": _w((lambda *s: torch.randn(*s, dtype=torch.bfloat16) * 0.1)(H, D, M) * ((H * D) ** -0.5)),
        }
    _B_in = _B_setup()

    return {
        "A_x": _A_in["x"],
        "A_k_cache": _A_in["k_cache"],
        "A_v_cache": _A_in["v_cache"],
        "A_wq": _A_in["wq"],
        "A_wo": _A_in["wo"],
        "B_x": _B_in["x"],
        "B_c_kv": _B_in["c_kv"],
        "B_w_q": _B_in["w_q"],
        "B_w_uk": _B_in["w_uk"],
        "B_w_uv": _B_in["w_uv"],
        "B_w_o": _B_in["w_o"],
    }

def reference(A_x, A_k_cache, A_v_cache, A_wq, A_wo, B_x, B_c_kv, B_w_q, B_w_uk, B_w_uv, B_w_o):
    def _A_ref(x, k_cache, v_cache, wq, wo):
        B, Sq, D = x.shape
        Hq, Dh = 32, 128
        Hkv = k_cache.shape[1]
        rep = Hq // Hkv
        q = (lambda x, *d: x.permute(*d))((x @ wq).reshape(B, Sq, Hq, Dh), 0, 2, 1, 3)
        k = (lambda x, n, axis: torch.repeat_interleave(x, n, dim=axis))(k_cache, rep, axis=1)
        v = (lambda x, n, axis: torch.repeat_interleave(x, n, dim=axis))(v_cache, rep, axis=1)
        scores = torch.einsum("bhqd,bhkd->bhqk", q, k) * (Dh ** -0.5)
        p = _softmax(scores, axis=-1)
        o = torch.einsum("bhqk,bhkd->bhqd", p, v)
        return (lambda x, *d: x.permute(*d))(o, 0, 2, 1, 3).reshape(B, Sq, Hq * Dh) @ wo

    def _B_ref(x, c_kv, w_q, w_uk, w_uv, w_o):
        B, Sq, M = x.shape[0], x.shape[1], x.shape[2]
        Sk = c_kv.shape[1]
        H, D = w_q.shape[1], w_q.shape[2]
        q = torch.einsum("bqm,mhd->bhqd", x, w_q)
        k = torch.einsum("bkc,chd->bhkd", c_kv, w_uk)
        v = torch.einsum("bkc,chd->bhkd", c_kv, w_uv)
        scores = torch.einsum("bhqd,bhkd->bhqk", q, k) * (D ** -0.5)
        off = Sk - Sq
        qi = torch.arange(Sq)[:, None]
        kj = torch.arange(Sk)[None, :]
        cmask = kj <= (qi + off)
        scores = torch.where(cmask[None, None], scores, -1e9)
        p = _softmax(scores, axis=-1)
        ctx = torch.einsum("bhqk,bhkd->bhqd", p, v)
        return torch.einsum("bhqd,hdm->bqm", ctx, w_o)

    a = _A_ref(A_x, A_k_cache, A_v_cache, A_wq, A_wo)
    b = _B_ref(B_x, B_c_kv, B_w_q, B_w_uk, B_w_uv, B_w_o)
    return torch.concatenate([a, b], axis=-1)
```

```cpp
#include <cuda_runtime.h>
#include <cuda_bf16.h>
#include <cuda.h>
#include <stdint.h>

namespace {

constexpr int NT       = 8192;
constexpr int GRID     = 132;
constexpr int NB_CTA   = 16;
constexpr int NA_CTA   = GRID - NB_CTA;
constexpr int NWORK    = 3;
#define YV 290
#define DV 56
#define JE0 112
#define VPROMO CU_TENSOR_MAP_L2_PROMOTION_L2_256B
#define YB 582
#define YW 407
#define DW 68
#define YX 150
#define YP 605
#define YPS 0
#define XU 2
#define RA 2
#define PR 64
#define PV 128
#define DL 6
#define WPROMO CU_TENSOR_MAP_L2_PROMOTION_L2_256B
#define XRV 330
#define TV 3200
#define PFB 8192
#define LAGT 1060
#define YLATE 120
#define YSL 70
#define YO 450
#define YOS 40
#define TUV (43 * 128)
#define XPK 80
#define FRZ 60
#define QDELAY 500
constexpr int NEARX = 400;
constexpr int HCLR  = 26;
constexpr int BINFL = 2;
constexpr int NSTATIC  = NA_CTA * NWORK;
constexpr unsigned DRAWS = (NT - NSTATIC) + GRID * NWORK;
static_assert(52 * 128 + LAGT + 300 <= NT && TUV + 10 * 128 <= NT, "wait_prog thresholds must be reachable");
constexpr int NTHREADS = 256;
constexpr float SCALE = 0.08838834764831845f, LOG2E = 1.4426950408889634f;
constexpr unsigned SPIN_LIMIT = 1u << 22;

constexpr int SM_SLOT  = 0;
constexpr int SM_QA    = 196608;
constexpr int SM_P     = SM_QA + 16384;
constexpr int SM_RED1  = SM_P + 4096;
constexpr int SM_RED2  = SM_RED1 + 2048;
constexpr int SM_VEC   = SM_RED2 + 4096;
constexpr int SM_BAR   = SM_VEC + 3072;
constexpr int SM_TOTAL = SM_BAR + 352;
constexpr int V_X    = 512;
constexpr int BAR_FULL = 0;
constexpr int BAR_PDONE= 48;
constexpr int BAR_BDONE= 56;
constexpr int BAR_QABS = 72;
constexpr int BAR_BFULL= 80;
constexpr int BAR_BEMPTY=120;
constexpr int BAR_WFREE= 160;
constexpr int BAR_W    = 168;
constexpr int BAR_S    = 192;
constexpr int BAR_Q    = 264;
constexpr int W_EPOCH  = 328;
constexpr int W_PROG   = 336;
constexpr int SM_WQ = 3 * 32768, SM_WQB = 4 * 32768, SM_WUK = 5 * 32768;
constexpr int SM_SQ = 3 * 32768;
constexpr int XSTR = 1024 + 16;

struct __align__(128) Cnt { unsigned v; unsigned pad[31]; };
struct __align__(128) Scratch {
    Cnt epoch, ticket, cntQabs, cntB;
    float qA[64 * 128], qB[64 * 128];
    __nv_bfloat16 qabs[2 * 32 * 512];
    float  partO[NT * 128];
    float2 partML[NT * 4];
    float  bpart[NB_CTA * 32 * 512];
    float2 bml[NB_CTA * 32];
    float  ctx[32 * 4 * 2 * 128];
    float  o[2 * 4096];
};
__device__ __align__(128) unsigned char g_raw[sizeof(Scratch)];

__device__ __forceinline__ int slice_of(int cta) {
    const int r = (cta >> 2) & 3, s = cta >> 4;
    const int grp = (r & 1) ? (r == 1 ? s : (s >> 1) + ((s & 1) ? 8 : 28)) : 12 + 4 * r + s;
    return cta >= 128 ? cta : 4 * grp + (cta & 3);
}

#define STAMP(cond, i) do {} while (0)
#define LAND(cond, i) do {} while (0)

__device__ __forceinline__ void mbar_init(uint32_t bar, int cnt) {
    asm volatile("mbarrier.init.shared::cta.b64 [%0], %1;" ::"r"(bar), "r"(cnt) : "memory");
}
__device__ __forceinline__ void mbar_expect_tx(uint32_t bar, uint32_t bytes) {
    asm volatile("mbarrier.arrive.expect_tx.shared::cta.b64 _, [%0], %1;" ::"r"(bar), "r"(bytes) : "memory");
}
__device__ __forceinline__ void mbar_arrive(uint32_t bar) {
    asm volatile("mbarrier.arrive.shared::cta.b64 _, [%0];" ::"r"(bar) : "memory");
}
__device__ __forceinline__ void mbar_wait(uint32_t bar, uint32_t parity) {
    unsigned it = 0;
    while (true) {
        uint32_t ok;
        asm volatile("{\n.reg .pred p;\nmbarrier.try_wait.parity.shared::cta.b64 p, [%1], %2;\nselp.u32 %0, 1, 0, p;\n}\n"
                     : "=r"(ok) : "r"(bar), "r"(parity) : "memory");
        if (ok) break;
        if (++it > SPIN_LIMIT) __trap();
    }
}
__device__ __forceinline__ void mbar_wait_nt(uint32_t bar, uint32_t parity) {
#pragma unroll 1
    for (unsigned it = 0; it < SPIN_LIMIT; it++) {
        uint32_t ok;
        asm volatile("{\n.reg .pred p;\nmbarrier.try_wait.parity.shared::cta.b64 p, [%1], %2;\nselp.u32 %0, 1, 0, p;\n}\n"
                     : "=r"(ok) : "r"(bar), "r"(parity) : "memory");
        if (ok) break;
    }
}
__device__ __forceinline__ bool mbar_test(uint32_t bar, uint32_t parity) {
    uint32_t ok;
    asm volatile("{\n.reg .pred p;\nmbarrier.test_wait.parity.shared::cta.b64 p, [%1], %2;\nselp.u32 %0, 1, 0, p;\n}\n"
                 : "=r"(ok) : "r"(bar), "r"(parity) : "memory");
    return ok;
}
__device__ __forceinline__ void bulk_load(uint32_t dst, const void* src, uint32_t bytes, uint32_t bar, uint64_t pol) {
    asm volatile("cp.async.bulk.shared::cluster.global.mbarrier::complete_tx::bytes.L2::cache_hint [%0], [%1], %2, [%3], %4;"
                 ::"r"(dst), "l"(src), "r"(bytes), "r"(bar), "l"(pol) : "memory");
}
__device__ __forceinline__ void bulk_load_nohint(uint32_t dst, const void* src, uint32_t bytes, uint32_t bar) {
    asm volatile("cp.async.bulk.shared::cluster.global.mbarrier::complete_tx::bytes [%0], [%1], %2, [%3];"
                 ::"r"(dst), "l"(src), "r"(bytes), "r"(bar) : "memory");
}
__device__ __forceinline__ void tma_2d(uint32_t dst, const CUtensorMap* map, int c0, int c1, uint32_t bar, uint64_t pol) {
    asm volatile("cp.async.bulk.tensor.2d.shared::cluster.global.mbarrier::complete_tx::bytes.L2::cache_hint [%0], [%1, {%3, %4}], [%2], %5;"
                 ::"r"(dst), "l"(map), "r"(bar), "r"(c0), "r"(c1), "l"(pol) : "memory");
}
__device__ __forceinline__ void tma_3d(uint32_t dst, const CUtensorMap* map, int c1, int c2, uint32_t bar, uint64_t pol) {
    asm volatile("cp.async.bulk.tensor.3d.shared::cluster.global.mbarrier::complete_tx::bytes.L2::cache_hint [%0], [%1, {%3, %4, %5}], [%2], %6;"
                 ::"r"(dst), "l"(map), "r"(bar), "r"(0), "r"(c1), "r"(c2), "l"(pol) : "memory");
}
__device__ __forceinline__ void wait_prog(const unsigned char* smem_word, unsigned th) {
    unsigned it = 0;
    while (*(volatile const unsigned*)(smem_word + 8) + NSTATIC < th) {
        __nanosleep(60);
        if (++it > SPIN_LIMIT) __trap();
    }
}
__device__ __forceinline__ uint32_t now_ns() {
    uint32_t t;
    asm volatile("mov.u32 %0, %globaltimer_lo;" : "=r"(t) :: "memory");
    return t;
}
__device__ __forceinline__ void note_draw(unsigned char* smem_word, unsigned raw) {
    const uint32_t a = (uint32_t)__cvta_generic_to_shared(smem_word);
    asm volatile("st.volatile.u32 [%0], %1;" ::"l"(smem_word + 8), "r"(raw) : "memory");
    const uint32_t now = now_ns();
    if ((int)raw < NT - NSTATIC - FRZ) asm volatile("st.volatile.shared.v2.u32 [%0], {%1, %2};" ::"r"(a), "r"(raw), "r"(now) : "memory");
}
__device__ __forceinline__ void wait_ticket(const unsigned char* smem_word, int th, int ahead = 0) {
    wait_prog(smem_word, min(th - ahead, NT - NEARX));
    uint32_t tk, t0;
#pragma unroll 1
    for (unsigned it = 0; it < SPIN_LIMIT; it++) {
        asm volatile("ld.volatile.shared.v2.u32 {%0, %1}, [%2];" : "=r"(tk), "=r"(t0) : "r"((uint32_t)__cvta_generic_to_shared(smem_word)) : "memory");
        if ((int)(now_ns() - t0) >= (th - NSTATIC - (int)tk) * 10) break;
        __nanosleep(20);
    }
}
__device__ __forceinline__ bool mbar_wait_for(uint32_t bar, uint32_t parity, int n) {
    uint32_t c0, c;
    asm volatile("mov.u32 %0, %%clock;" : "=r"(c0) :: "memory");
    do {
        if (mbar_test(bar, parity)) return true;
        asm volatile("mov.u32 %0, %%clock;" : "=r"(c) :: "memory");
    } while ((int)(c - c0) < n);
    return false;
}
__device__ __forceinline__ bool elect_one() {
    uint32_t p;
    asm volatile("{\n.reg .pred p;\nelect.sync _|p, 0xffffffff;\nselp.u32 %0, 1, 0, p;\n}\n" : "=r"(p));
    return p;
}
__device__ __forceinline__ void fence_proxy_async() { asm volatile("fence.proxy.async;" ::: "memory"); }
__device__ __forceinline__ void named_bar(int id, int n) { asm volatile("bar.sync %0, %1;" ::"r"(id), "r"(n) : "memory"); }

__device__ __forceinline__ uint4 lds128(uint32_t a) {
    uint4 v;
    asm volatile("ld.shared.v4.u32 {%0,%1,%2,%3}, [%4];" : "=r"(v.x), "=r"(v.y), "=r"(v.z), "=r"(v.w) : "r"(a));
    return v;
}
__device__ __forceinline__ uint4 ldsm4(uint32_t a) {
    uint4 v;
    asm volatile("ldmatrix.sync.aligned.m8n8.x4.shared.b16 {%0,%1,%2,%3}, [%4];" : "=r"(v.x), "=r"(v.y), "=r"(v.z), "=r"(v.w) : "r"(a));
    return v;
}
__device__ __forceinline__ uint4 ldsm4t(uint32_t a) {
    uint4 v;
    asm volatile("ldmatrix.sync.aligned.m8n8.x4.trans.shared.b16 {%0,%1,%2,%3}, [%4];" : "=r"(v.x), "=r"(v.y), "=r"(v.z), "=r"(v.w) : "r"(a));
    return v;
}
__device__ __forceinline__ uint2 lds64(uint32_t a) {
    uint2 v;
    asm volatile("ld.shared.v2.u32 {%0,%1}, [%2];" : "=r"(v.x), "=r"(v.y) : "r"(a));
    return v;
}
__device__ __forceinline__ uint4 ld_relaxed128(const void* p) {
    uint4 v;
    asm volatile("ld.relaxed.gpu.global.v4.u32 {%0,%1,%2,%3}, [%4];" : "=r"(v.x), "=r"(v.y), "=r"(v.z), "=r"(v.w) : "l"(p) : "memory");
    return v;
}
__device__ __forceinline__ uint2 ld_relaxed64(const void* p) {
    uint2 v;
    asm volatile("ld.relaxed.gpu.global.v2.u32 {%0,%1}, [%2];" : "=r"(v.x), "=r"(v.y) : "l"(p) : "memory");
    return v;
}
__device__ __forceinline__ uint32_t ld_relaxed32(const void* p) {
    uint32_t v;
    asm volatile("ld.relaxed.gpu.global.u32 %0, [%1];" : "=r"(v) : "l"(p) : "memory");
    return v;
}
__device__ __forceinline__ uint32_t ld_acquire32(const void* p) {
    uint32_t v;
    asm volatile("ld.acquire.gpu.global.u32 %0, [%1];" : "=r"(v) : "l"(p) : "memory");
    return v;
}
__device__ __forceinline__ void st_relaxed128(void* p, uint32_t a, uint32_t b, uint32_t c, uint32_t d) {
    asm volatile("st.relaxed.gpu.global.v4.u32 [%0], {%1,%2,%3,%4};" ::"l"(p), "r"(a), "r"(b), "r"(c), "r"(d) : "memory");
}
__device__ __forceinline__ void st_relaxed64(void* p, uint32_t a, uint32_t b) {
    asm volatile("st.relaxed.gpu.global.v2.u32 [%0], {%1,%2};" ::"l"(p), "r"(a), "r"(b) : "memory");
}
__device__ __forceinline__ void red_release(unsigned* p) {
    asm volatile("red.release.gpu.global.add.u32 [%0], 1;" ::"l"(p) : "memory");
}
__device__ __forceinline__ void wait_counter(const unsigned* p, unsigned target, unsigned ns) {
    unsigned it = 0;
    while ((int)(ld_acquire32(p) - target) < 0) {
        __nanosleep(ns);
        if (++it > SPIN_LIMIT) __trap();
    }
}
__device__ __forceinline__ uint32_t prmt(uint32_t a, uint32_t b, uint32_t s) {
    uint32_t d;
    asm("prmt.b32 %0, %1, %2, %3;" : "=r"(d) : "r"(a), "r"(b), "r"(s));
    return d;
}
__device__ __forceinline__ uint32_t pack_bf16(float lo, float hi) {
    uint32_t d;
    asm("cvt.rn.bf16x2.f32 %0, %1, %2;" : "=r"(d) : "f"(hi), "f"(lo));
    return d;
}
__device__ __forceinline__ float ex2(float x) {
    float y;
    asm("ex2.approx.ftz.f32 %0, %1;" : "=f"(y) : "f"(x));
    return y;
}
__device__ __forceinline__ float bf_lo(uint32_t v) { return __uint_as_float(v << 16); }
__device__ __forceinline__ float bf_hi(uint32_t v) { return __uint_as_float(v & 0xffff0000u); }
__device__ __forceinline__ void scale_scores(float& a, float& b) {
    uint32_t p = pack_bf16(a, b);
    p = pack_bf16(bf_lo(p) * SCALE, bf_hi(p) * SCALE);
    a = bf_lo(p); b = bf_hi(p);
}
__device__ __forceinline__ uint32_t tagw(float v, uint32_t tag) {
    uint32_t d;
    asm("lop3.b32 %0, %1, 0xfffffffe, %2, 0xEA;" : "=r"(d) : "r"(__float_as_uint(v)), "r"(tag));
    return d;
}
__device__ __forceinline__ uint32_t bad2(uint32_t x, uint32_t y, uint32_t tag) {
    uint32_t d;
    asm("lop3.b32 %0, %1, %2, %3, 0x7E;" : "=r"(d) : "r"(x), "r"(y), "r"(tag));
    return d;
}
__device__ __forceinline__ uint32_t bad4(const uint4& v, uint32_t tag) { return bad2(v.x, v.y, tag) | bad2(v.z, v.w, tag); }
__device__ __forceinline__ void ld_relaxed128_if(uint4& v, const void* p, uint32_t c) {
    asm volatile("{\n.reg .pred p;\nsetp.ne.u32 p, %5, 0;\n@p ld.relaxed.gpu.global.v4.u32 {%0,%1,%2,%3}, [%4];\n}\n"
                 : "+r"(v.x), "+r"(v.y), "+r"(v.z), "+r"(v.w) : "l"(p), "r"(c) : "memory");
}
__device__ __forceinline__ void ld_relaxed64_if(uint2& v, const void* p, uint32_t c) {
    asm volatile("{\n.reg .pred p;\nsetp.ne.u32 p, %3, 0;\n@p ld.relaxed.gpu.global.v2.u32 {%0,%1}, [%2];\n}\n"
                 : "+r"(v.x), "+r"(v.y) : "l"(p), "r"(c) : "memory");
}
__device__ __forceinline__ void st_relaxed32(void* p, uint32_t a) {
    asm volatile("st.relaxed.gpu.global.u32 [%0], %1;" ::"l"(p), "r"(a) : "memory");
}
__device__ __forceinline__ void red_out(uint32_t* word, float v, int col, uint32_t go) {
    const uint32_t pk = (col & 1) ? pack_bf16(-0.f, v) : pack_bf16(v, -0.f);
    asm volatile("{\n.reg .pred p;\nsetp.ne.u32 p, %2, 0;\n@p red.relaxed.gpu.global.add.noftz.bf16x2 [%0], %1;\n}\n"
                 ::"l"(word), "r"(pk), "r"(go) : "memory");
}
__device__ __forceinline__ void mma16816(float (&c)[4], uint32_t a0, uint32_t a1, uint32_t a2, uint32_t a3,
                                         uint32_t b0, uint32_t b1) {
    asm("mma.sync.aligned.m16n8k16.row.col.f32.bf16.bf16.f32 {%0,%1,%2,%3}, {%4,%5,%6,%7}, {%8,%9}, {%0,%1,%2,%3};"
        : "+f"(c[0]), "+f"(c[1]), "+f"(c[2]), "+f"(c[3])
        : "r"(a0), "r"(a1), "r"(a2), "r"(a3), "r"(b0), "r"(b1));
}
__device__ __forceinline__ uint64_t make_desc(uint32_t addr) {
    return (uint64_t)((addr & 0x3FFFF) >> 4) | ((uint64_t)1 << 16) | ((uint64_t)64 << 32) | ((uint64_t)1 << 62);
}
template <int TRANS_A>
__device__ __forceinline__ void wgmma_n32(float (&d)[16], uint64_t da, uint64_t db, int scale_d) {
    asm volatile("{\n.reg .pred p;\nsetp.ne.b32 p, %18, 0;\n"
                 "wgmma.mma_async.sync.aligned.m64n32k16.f32.bf16.bf16 "
                 "{%0,%1,%2,%3,%4,%5,%6,%7,%8,%9,%10,%11,%12,%13,%14,%15}, %16, %17, p, 1, 1, %19, 0;\n}\n"
                 : "+f"(d[0]), "+f"(d[1]), "+f"(d[2]), "+f"(d[3]), "+f"(d[4]), "+f"(d[5]), "+f"(d[6]), "+f"(d[7]),
                   "+f"(d[8]), "+f"(d[9]), "+f"(d[10]), "+f"(d[11]), "+f"(d[12]), "+f"(d[13]), "+f"(d[14]), "+f"(d[15])
                 : "l"(da), "l"(db), "r"(scale_d), "n"(TRANS_A));
}
__device__ __forceinline__ void wg_fence()  { asm volatile("wgmma.fence.sync.aligned;" ::: "memory"); }
__device__ __forceinline__ void wg_commit() { asm volatile("wgmma.commit_group.sync.aligned;" ::: "memory"); }
template <int N> __device__ __forceinline__ void wg_wait() { asm volatile("wgmma.wait_group.sync.aligned %0;" ::"n"(N) : "memory"); }

__device__ __forceinline__ void issue_tall(uint32_t dst, const CUtensorMap* map, int col, int row, uint32_t bar, uint64_t pol) {
    tma_2d(dst, map, col, row, bar, pol);
    tma_2d(dst + 16384, map, col, row + 256, bar, pol);
}
__device__ __forceinline__ void tall_prep(uint2 (&bf)[16], uint32_t xbase, int w4, int g, int t) {
    const uint32_t xp = xbase + ((g >> 1) & 1) * 1024 + w4 * 256 + (t >> 1) * 8;
    const uint32_t sel = (g & 1) ? ((t & 1) ? 0x3244u : 0x1044u) : ((t & 1) ? 0x4432u : 0x4410u);
#pragma unroll
    for (int i = 0; i < 16; i++) {
        const uint2 xw = lds64(xp + i * 16);
        bf[i] = make_uint2(prmt(xw.x, 0, sel), prmt(xw.y, 0, sel));
    }
}
__device__ __forceinline__ void gemv_tall(uint32_t wbase, const uint2 (&bf)[16], float* red, int w4, int g, int t) {
    const uint32_t wu = wbase + (128 * w4 + (t & 1) + 4 * (t >> 1)) * 64 + (((g >> 1) ^ (t & 2)) << 4) + (g & 1) * 8;
    const uint32_t wv = (wu + 128) ^ 16;
    float a[4][4];
#pragma unroll
    for (int i = 0; i < 16; i++) (&a[0][0])[i] = 0.f;
#pragma unroll
    for (int i = 0; i < 16; i++) {
        const uint2 u = lds64(wu + i * 512), v = lds64(wv + i * 512);
        mma16816(a[i & 3], u.x, u.y, v.x, v.y, bf[i].x, bf[i].y);
    }
    if (t < 2)
        *(float4*)(red + (w4 * 2 + t) * 32 + 4 * g) =
            make_float4((a[0][0] + a[1][0]) + (a[2][0] + a[3][0]), (a[0][1] + a[1][1]) + (a[2][1] + a[3][1]),
                        (a[0][2] + a[1][2]) + (a[2][2] + a[3][2]), (a[0][3] + a[1][3]) + (a[2][3] + a[3][3]));
}
__device__ __forceinline__ void tall_finish(const float* red, float* dst, int tid, uint32_t tag, int lo = 0, int hi = 64) {
    named_bar(1, 128);
    if (tid >= lo && tid < hi) {
        st_relaxed32(dst, tagw((red[tid] + red[64 + tid]) + (red[128 + tid] + red[192 + tid]), tag));
    }
}

__device__ __forceinline__ void combineA(Scratch& G, int bh, int dq, uint32_t tag, float* red, int tid, const unsigned char* prog) {
    const int r = tid >> 3, c4 = tid & 7, w4 = tid >> 5, lane = tid & 31;
    const float2* ml = G.partML + (bh * 128 + r) * 4;
    const float* po = G.partO + (size_t)(bh * 128 + r) * 128 + dq * 32 + c4 * 4;
    uint2 m[8];
    uint4 o[8];
    uint32_t bad[8];
    STAMP(tid == 0 && bh >= 32, 28);
#pragma unroll
    for (int k = 0; k < 8; k++) m[k] = ld_relaxed64(ml + 64 * k);
#pragma unroll
    for (int k = 0; k < 8; k++) {
        o[k] = make_uint4(~tag, ~tag, ~tag, ~tag);
        ld_relaxed128_if(o[k], po + (size_t)k * 16 * 128, bh < 60);
    }
    unsigned it = 0;
    while (true) {
        uint32_t any = 0;
#pragma unroll
        for (int k = 0; k < 8; k++) { bad[k] = bad2(m[k].x, m[k].y, tag) & 1u; any |= bad[k]; }
        if (!__any_sync(~0u, any)) break;
#pragma unroll
        for (int k = 0; k < 8; k++) ld_relaxed64_if(m[k], ml + 64 * k, bad[k]);
        if (++it > SPIN_LIMIT) __trap();
    }
    STAMP(tid == 0 && bh >= 32, 30);
    STAMP(tid == 0 && bh >= 32, 19);
    float M = fmaxf(fmaxf(fmaxf(__uint_as_float(m[0].x), __uint_as_float(m[1].x)), fmaxf(__uint_as_float(m[2].x), __uint_as_float(m[3].x))),
                    fmaxf(fmaxf(__uint_as_float(m[4].x), __uint_as_float(m[5].x)), fmaxf(__uint_as_float(m[6].x), __uint_as_float(m[7].x))));
    M = fmaxf(M, __shfl_xor_sync(~0u, M, 8));
    M = fmaxf(M, __shfl_xor_sync(~0u, M, 16));
    float wgt[8], L = 0.f;
#pragma unroll
    for (int k = 0; k < 8; k++) {
        wgt[k] = ex2(__uint_as_float(m[k].x) - M);
        L = fmaf(wgt[k], __uint_as_float(m[k].y), L);
    }
    L += __shfl_xor_sync(~0u, L, 8);
    L += __shfl_xor_sync(~0u, L, 16);
    if (lane == 0) { red[128 + w4] = M; red[132 + w4] = L; }
    named_bar(1, 128);
    {
        const float4 Mw = *(float4*)(red + 128), Lw = *(float4*)(red + 132);
        const float Mx = fmaxf(fmaxf(Mw.x, Mw.y), fmaxf(Mw.z, Mw.w));
        const float Lt = (ex2(Mw.x - Mx) * Lw.x + ex2(Mw.y - Mx) * Lw.y) + (ex2(Mw.z - Mx) * Lw.z + ex2(Mw.w - Mx) * Lw.w);
        const float f = ex2(M - Mx) / Lt;
#pragma unroll
        for (int k = 0; k < 8; k++) wgt[k] *= f;
    }
    STAMP(tid == 0 && bh >= 32, 23);
    if (bh >= 60) wait_ticket(prog, NT + YO + (bh - 63) * YOS);
    while (true) {
        uint32_t any = 0;
#pragma unroll
        for (int k = 0; k < 8; k++) { bad[k] = bad4(o[k], tag) & 1u; any |= bad[k]; }
        if (!__any_sync(~0u, any)) break;
#pragma unroll
        for (int k = 0; k < 8; k++) ld_relaxed128_if(o[k], po + (size_t)k * 16 * 128, bad[k]);
        if (++it > SPIN_LIMIT) __trap();
    }
    STAMP(tid == 0 && bh >= 32, 31);
    float a0 = 0.f, a1 = 0.f, a2 = 0.f, a3 = 0.f, b0 = 0.f, b1 = 0.f, b2 = 0.f, b3 = 0.f;
#pragma unroll
    for (int k = 0; k < 8; k += 2) {
        a0 = fmaf(wgt[k], __uint_as_float(o[k].x), a0); b0 = fmaf(wgt[k + 1], __uint_as_float(o[k + 1].x), b0);
        a1 = fmaf(wgt[k], __uint_as_float(o[k].y), a1); b1 = fmaf(wgt[k + 1], __uint_as_float(o[k + 1].y), b1);
        a2 = fmaf(wgt[k], __uint_as_float(o[k].z), a2); b2 = fmaf(wgt[k + 1], __uint_as_float(o[k + 1].z), b2);
        a3 = fmaf(wgt[k], __uint_as_float(o[k].w), a3); b3 = fmaf(wgt[k + 1], __uint_as_float(o[k + 1].w), b3);
    }
    a0 += b0; a1 += b1; a2 += b2; a3 += b3;
#pragma unroll
    for (int s = 8; s <= 16; s <<= 1) {
        a0 += __shfl_xor_sync(~0u, a0, s);
        a1 += __shfl_xor_sync(~0u, a1, s);
        a2 += __shfl_xor_sync(~0u, a2, s);
        a3 += __shfl_xor_sync(~0u, a3, s);
    }
    if (lane < 8) *(float4*)(red + w4 * 32 + c4 * 4) = make_float4(a0, a1, a2, a3);
    named_bar(1, 128);
    STAMP(tid == 0 && bh >= 32, 24);
}

struct Ptrs {
    const __nv_bfloat16 *K, *xA, *xB;
    __nv_bfloat16* out;
    Scratch* g;
};
struct Maps { CUtensorMap m_wq, m_v, m_ckv, m_wqB, m_wuk, m_uv[2], m_w[2]; };

__global__ void __launch_bounds__(NTHREADS, 1)
fused_decode_kernel(const Ptrs P, const __grid_constant__ Maps M) {
    extern __shared__ __align__(1024) unsigned char smem[];
    const uint32_t sb = (uint32_t)__cvta_generic_to_shared(smem);
    uint64_t pol;
    asm("createpolicy.fractional.L2::evict_first.b64 %0, 1.0;" : "=l"(pol));
    asm volatile("{\n.reg .pred p;\nsetp.lt.u32 p, %3, 32;\n@p cp.async.bulk.prefetch.L2.global.L2::cache_hint [%0], %1, %2;\n}\n"
                 ::"l"((const char*)P.K + (blockIdx.x << 14)), "n"(PFB), "l"(pol), "r"(threadIdx.x) : "memory");
    if (threadIdx.x < 32 && elect_one()) {
        mbar_init(sb + SM_BAR + BAR_FULL, 1);
        mbar_init(sb + SM_BAR + BAR_W, 1);
        asm volatile("fence.mbarrier_init.release.cluster;" ::: "memory");
        if (blockIdx.x < NA_CTA) {
            mbar_expect_tx(sb + SM_BAR + BAR_FULL, 16384);
            bulk_load(sb + SM_SLOT, (const char*)P.K + (blockIdx.x << 14), 16384, sb + SM_BAR + BAR_FULL, pol);
        }
        if (blockIdx.x < 128) {
            mbar_expect_tx(sb + SM_BAR + BAR_W, 32768 + 4096);
            issue_tall(sb + SM_WQ, &M.m_wq, slice_of(blockIdx.x) * 32, 0, sb + SM_BAR + BAR_W, pol);
            bulk_load_nohint(sb + SM_P, P.xA, 2048, sb + SM_BAR + BAR_W);
            bulk_load_nohint(sb + SM_P + 2048, P.xB, 2048, sb + SM_BAR + BAR_W);
        }
    }
    const int tid = threadIdx.x, warp = __shfl_sync(~0u, tid >> 5, 0), lane = tid & 31;
    const int g = lane >> 2, t = lane & 3;
    const int cta = blockIdx.x;
    Scratch& G = *P.g;
    const bool isB = cta >= NA_CTA;
    const bool hasSlice = cta < 128;
    const int j = slice_of(cta), h = j >> 2, qd = cta & 3;
    const int mat = j >> 6, cg = j & 7, rg = (j >> 3) & 7;
    const bool late = j < JE0 || j >= 124;
    STAMP(tid == 32, 0);
    if (warp == 7) {
        __syncthreads();
        const uint32_t epoch = *(volatile uint32_t*)(smem + SM_BAR + W_EPOCH);
        const uint32_t tag = (epoch + 1) & 1;
        if (!isB) { mbar_wait(sb + SM_BAR + BAR_W, 0); __nanosleep(QDELAY); }
#pragma unroll 1
        for (int i = 0; i < 8; i++) {
            if (i == 4 && !isB) wait_prog(smem + SM_BAR + W_PROG, 16 * 128);
            if (i == 0 && isB) { mbar_wait(sb + SM_BAR + BAR_QABS, 0); __nanosleep(8000); }
            uint4 v[8];
            uint32_t bad[8];
#pragma unroll
            for (int k = 0; k < 8; k++) { bad[k] = 1; v[k] = make_uint4(0, 0, 0, 0); }
            unsigned it = 0;
            while (true) {
#pragma unroll
                for (int k = 0; k < 8; k++) ld_relaxed128_if(v[k], G.qA + (8 * i + k) * 128 + lane * 4, bad[k]);
                uint32_t any = 0;
#pragma unroll
                for (int k = 0; k < 8; k++) { bad[k] = bad4(v[k], tag) & 1u; any |= bad[k]; }
                if (!__any_sync(~0u, any)) break;
                __nanosleep(40);
                if (++it > SPIN_LIMIT) __trap();
            }
#pragma unroll
            for (int k = 0; k < 8; k++) {
                uint32_t* dst = (uint32_t*)(smem + SM_QA + (8 * i + k) * 256 + (lane >> 1) * 16 + (lane & 1) * 4);
                dst[0] = pack_bf16(__uint_as_float(v[k].x), __uint_as_float(v[k].y));
                dst[2] = pack_bf16(__uint_as_float(v[k].z), __uint_as_float(v[k].w));
            }
            __syncwarp();
            if (lane == 0) mbar_arrive(sb + SM_BAR + BAR_Q + i * 8);
            STAMP(lane == 0 && i == 0, 2);
        }
        STAMP(lane == 0, 21);
        if (hasSlice && lane == 0) {
            mbar_wait(sb + SM_BAR + BAR_PDONE, 0);
#pragma unroll 1
            for (int p = 0; p < 512 / PV + 512 / PR; p++) {
                const bool uv = p < 512 / PV;
                const int r = uv ? p * PV : (p - 512 / PV) * PR;
                if (!uv || late)
                    wait_ticket(smem + SM_BAR + W_PROG, NT + (uv ? YV + (r * DV >> 8) : YW + (r * DW >> 7) + (r + PR == 512 ? DL : 0)));
                STAMP(p == 0, 10);
                const bool tail = !uv && r >= 384 + 32 * RA;
                const uint32_t bar = sb + SM_BAR + BAR_S + (uv ? r >> 8 : (tail ? 6 : 2 + (r >> 7))) * 8;
                if (uv ? (r & 255) == 0 : ((r & 127) == 0 || r == 384 + 32 * RA))
                    mbar_expect_tx(bar, uv || r < 384 ? 16384 : (tail ? (4 - RA) * 4096 : RA * 4096));
                tma_2d(sb + SM_SQ + (uv ? r * 64 : 32768 + r * 128), uv ? &M.m_uv[late] : &M.m_w[mat], uv ? j * 32 : cg * 64,
                       uv ? r : (rg + 8 * (r >> 7)) * 128 + (r & 127), bar, pol);
            }
        }
    } else if (warp >= 4) {
        const int wi = warp - 4;
        const uint32_t slot = sb + SM_SLOT + wi * 32768;
        const uint32_t bar = sb + SM_BAR + BAR_FULL + wi * 16, barV = bar + 8;
        unsigned tk = wi * NA_CTA + cta;
        const int ev = wi;
        if (lane == 0) {
            if (wi) mbar_init(bar, 1);
            mbar_init(barV, 1);
            if (isB && wi == 0) {
                for (int s = 0; s < 5; s++) {
                    mbar_init(sb + SM_BAR + BAR_BFULL + s * 8, 1);
                    mbar_init(sb + SM_BAR + BAR_BEMPTY + s * 8, 4);
                }
            }
            asm volatile("fence.mbarrier_init.release.cluster;" ::: "memory");
        }
        __syncthreads();
        const uint32_t epoch = *(volatile uint32_t*)(smem + SM_BAR + W_EPOCH);
        const uint32_t tag = (epoch + 1) & 1;

        bool active = true;
        if (isB) {
            if (wi == 1 && lane == 0) {
                wait_counter(&G.cntQabs.v, (epoch + 1) * 128, 64);
                fence_proxy_async();
                mbar_expect_tx(sb + SM_BAR + BAR_QABS, 32768);
                bulk_load_nohint(sb + SM_SLOT + 5 * 32768, G.qabs + ((cta - NA_CTA) >> 3) * 16384, 32768, sb + SM_BAR + BAR_QABS);
            }
            if (wi == 0 && lane == 0) {
                const int ib = cta - NA_CTA;
                int s = 0, sl = 0; uint32_t ph = 1, phl = 0;
                for (int u = 0; u < 32; u++) {
                    if (u >= BINFL) {
                        mbar_wait(sb + SM_BAR + BAR_BFULL + sl * 8, phl);
                        LAND(true, 16384 + ib * 32 + u);
                        if (++sl == 5) { sl = 0; phl ^= 1; }
                    }
                    if (u == 3 && hasSlice) mbar_wait(sb + SM_BAR + BAR_WFREE, 0);
                    mbar_wait(sb + SM_BAR + BAR_BEMPTY + s * 8, ph);
                    const uint32_t fb = sb + SM_BAR + BAR_BFULL + s * 8;
                    const int row = (ib >> 3) * 8192 + ((u >> 1) * 8 + (ib & 7)) * 64;
                    mbar_expect_tx(fb, 32768);
                    for (int x = 0; x < 4; x++)
                        tma_2d(sb + SM_SLOT + s * 32768 + x * 8192, &M.m_ckv, ((u & 1) * 4 + x) * 64, row, fb, pol);
                    if (++s == 5) { s = 0; ph ^= 1; }
                }
            }
            __syncwarp();
            mbar_wait(sb + SM_BAR + BAR_BDONE, 0);
            if (lane == 0) tk = NSTATIC + atomicInc(&G.ticket.v, DRAWS - 1);
            tk = __shfl_sync(~0u, tk, 0);
            active = tk < NT;
        } else if (ev != 0) {
            __syncwarp();
            mbar_wait(sb + SM_BAR + BAR_W + (ev - 1) * 8, 0);
        }
        if (active) {
            if ((isB || ev != 0) && lane == 0) {
                mbar_expect_tx(bar, 16384);
                bulk_load(slot, (const char*)P.K + (size_t)tk * 16384, 16384, bar, pol);
            }
            const uint32_t kA = slot + g * 256 + t * 16 + (g & 1) * 64, kB = kA ^ 64;
            const uint32_t qo = t * 16 + ((g >> 1) & 1) * 64 + (g & 1) * 8;
            const uint32_t v0 = slot + 16384 + (2 * t) * 128 + ((g ^ (2 * t)) << 4), v1 = (v0 + 128) ^ 16;
            const uint32_t sl0 = (g & 1) ? 0x1044u : 0x4410u, sl1 = (g & 1) ? 0x3244u : 0x4432u;
            const uint32_t sa0 = (g & 2) ? 0x4444u : sl0, sa1 = (g & 2) ? 0x4444u : sl1;
            const uint32_t sb0 = (g & 2) ? sl0 : 0x4444u, sb1 = (g & 2) ? sl1 : 0x4444u;
            const int d0 = 64 * (t >> 1) + 8 * g + 4 * (t & 1);
            uint32_t ph = 0;
            while (true) {
                const uint32_t qa = sb + SM_QA + (tk >> 7) * 256 + qo;
                bool vout = false;
                if (XRV && lane == 0 && tk >= NT - XRV && !mbar_wait_for(bar, ph, TV)) {
                    mbar_expect_tx(barV, 16384);
                    tma_3d(slot + 16384, &M.m_v, tk * 64, 0, barV, pol);
                    vout = true;
                }
                if (XRV) __syncwarp();
                mbar_wait(bar, ph);
                LAND(lane == 0, tk);
                unsigned nxt = 0;
                if (lane == 0) {
                    if (!vout) {
                        mbar_expect_tx(barV, 16384);
                        tma_3d(slot + 16384, &M.m_v, tk * 64, 0, barV, pol);
                    }
                    asm volatile("atom.relaxed.gpu.global.inc.u32 %0, [%1], %2;" : "=r"(nxt) : "l"(&G.ticket.v), "r"(DRAWS - 1) : "memory");
                }
                __syncwarp();
                mbar_wait(sb + SM_BAR + BAR_Q + (tk >> 10) * 8, 0);
                STAMP(tid == 128 && tk < NSTATIC, 3);
                uint2 qf[4];
                qf[0] = lds64(qa); qf[1] = lds64(qa ^ 64); qf[2] = lds64(qa + 128); qf[3] = lds64((qa ^ 64) + 128);
                float c[8][4];
#pragma unroll
                for (int i = 0; i < 32; i++) (&c[0][0])[i] = 0.f;
#pragma unroll
                for (int s = 0; s < 4; s++)
#pragma unroll
                    for (int jj = 0; jj < 8; jj++) {
                        const uint4 u = lds128(((s & 1) ? kB : kA) + jj * 2048 + (s >> 1) * 128);
                        mma16816(c[jj], u.x, u.y, u.z, u.w, qf[s].x, qf[s].y);
                    }
                float sc[8];
#pragma unroll
                for (int jj = 0; jj < 8; jj++) sc[jj] = c[jj][0] + c[jj][3];
#pragma unroll
                for (int jj = 0; jj < 8; jj += 2) scale_scores(sc[jj], sc[jj + 1]);
                float m = fmaxf(fmaxf(fmaxf(sc[0], sc[1]), fmaxf(sc[2], sc[3])), fmaxf(fmaxf(sc[4], sc[5]), fmaxf(sc[6], sc[7])));
                m = fmaxf(m, __shfl_xor_sync(~0u, m, 5));
                m = fmaxf(m, __shfl_xor_sync(~0u, m, 8));
                m = fmaxf(m, __shfl_xor_sync(~0u, m, 16));
                const float ms = __uint_as_float(tagw(m * LOG2E, tag));
                uint32_t W0[4], W1[4];
                float l = 0.f;
#pragma unroll
                for (int i = 0; i < 4; i++) {
                    const uint32_t pp = pack_bf16(ex2(fmaf(sc[2 * i], LOG2E, -ms)), ex2(fmaf(sc[2 * i + 1], LOG2E, -ms)));
                    W0[i] = __shfl_sync(~0u, pp, 8 * t);
                    W1[i] = __shfl_sync(~0u, pp, 8 * t + 5);
                    l += bf_lo(pp) + bf_hi(pp);
                }
                l += __shfl_xor_sync(~0u, l, 5);
                l += __shfl_xor_sync(~0u, l, 8);
                l += __shfl_xor_sync(~0u, l, 16);
                if (lane == 0 || lane == 2)
                    st_relaxed128((char*)G.partML + tk * 32 + lane * 8, __float_as_uint(ms), tagw(l, tag), __float_as_uint(ms), tagw(l, tag));
                uint32_t pb[16][2];
#pragma unroll
                for (int i = 0; i < 16; i++) {
                    const uint32_t pw = (i & 1) ? W1[i >> 2] : W0[i >> 2];
                    pb[i][0] = prmt(pw, 0, (i & 2) ? sa1 : sa0);
                    pb[i][1] = prmt(pw, 0, (i & 2) ? sb1 : sb0);
                    asm volatile("" : "+r"(pb[i][0]), "+r"(pb[i][1]));
                }
                float* po = G.partO + (size_t)tk * 128 + d0;
                asm volatile("" : "+l"(po));
                if (lane == 0) note_draw(smem + SM_BAR + W_PROG, nxt);
                nxt += NSTATIC;
                if (nxt >= NT - XPK && nxt < NT && lane == 0) {
                    mbar_expect_tx(bar, 16384);
                    bulk_load(slot, (const char*)P.K + (size_t)nxt * 16384, 16384, bar, pol);
                }
                mbar_wait(barV, ph);
                LAND(lane == 0, 8192 + tk);
                ph ^= 1;
                if (nxt < NT - XPK && lane == 0) {
                    mbar_expect_tx(bar, 16384);
                    bulk_load(slot, (const char*)P.K + (size_t)nxt * 16384, 16384, bar, pol);
                }
                __syncwarp();
                float acc[2][4][4];
#pragma unroll
                for (int i = 0; i < 32; i++) (&acc[0][0][0])[i] = 0.f;
#pragma unroll
                for (int jj = 0; jj < 8; jj++)
#pragma unroll
                    for (int e = 0; e < 2; e++)
#pragma unroll
                        for (int hh = 0; hh < 2; hh++) {
                            const uint4 u = lds128((e ? v1 : v0) + jj * 1024 + hh * 8192);
                            mma16816(acc[hh][(jj & 1) * 2 + e], u.x, u.y, u.z, u.w, pb[2 * jj + e][0], pb[2 * jj + e][1]);
                        }
                float r4[4];
#pragma unroll
                for (int i = 0; i < 4; i++) {
                    const float x0 = (acc[0][0][i] + acc[0][1][i]) + (acc[0][2][i] + acc[0][3][i]);
                    const float x1 = (acc[1][0][i] + acc[1][1][i]) + (acc[1][2][i] + acc[1][3][i]);
                    r4[i] = (t & 2) ? x1 : x0;
                }
                st_relaxed128(po, tagw(r4[0], tag), tagw(r4[1], tag), tagw(r4[2], tag), tagw(r4[3], tag));
                nxt = __shfl_sync(~0u, nxt, 0);
                if (nxt >= NT) break;
                tk = nxt;
            }
            STAMP(lane == 0, 16 + wi);
        } else if (lane == 0) {
            note_draw(smem + SM_BAR + W_PROG, tk - NSTATIC);
        }
    } else {
        float* red = (float*)(smem + SM_RED2);
        if (tid == 32) {
            const uint32_t ep0 = ld_relaxed32(&G.epoch.v);
            for (int e = 0; e < 8; e++) mbar_init(sb + SM_BAR + BAR_Q + e * 8, 1);
            for (int e = 1; e < 10; e++) mbar_init(sb + SM_BAR + BAR_W + e * 8, 1);
            mbar_init(sb + SM_BAR + BAR_BDONE, 1);
            mbar_init(sb + SM_BAR + BAR_PDONE, 1);
            mbar_init(sb + SM_BAR + BAR_QABS, 1);
            mbar_init(sb + SM_BAR + BAR_WFREE, 1);
            asm volatile("fence.mbarrier_init.release.cluster;" ::: "memory");
            asm volatile("st.volatile.shared.v4.u32 [%0], {%1, %2, %1, %1};" ::"r"(sb + SM_BAR + W_PROG), "r"(0), "r"(now_ns()) : "memory");
            *(volatile uint32_t*)(smem + SM_BAR + W_EPOCH) = ep0;
        } else if (tid == 64) {
            asm volatile("prefetch.tensormap [%0];" ::"l"(&M.m_v) : "memory");
            asm volatile("prefetch.tensormap [%0];" ::"l"(&M.m_wqB) : "memory");
            asm volatile("prefetch.tensormap [%0];" ::"l"(&M.m_wuk) : "memory");
        }
        __syncthreads();
        const uint32_t epoch = *(volatile uint32_t*)(smem + SM_BAR + W_EPOCH);
        const uint32_t tag = (epoch + 1) & 1;
        STAMP(tid == 0, 14);

        if (hasSlice) {
            const uint32_t nt = tag ^ 1;
            const int qoff = ((tid >> 5) & 1) * 4096 + 32 * j + (tid & 31);
            if (tid < 64) {
                st_relaxed32(G.qA + qoff, nt); st_relaxed32(G.qB + qoff, nt);
                if (tid < 32) {
                    st_relaxed32(G.o + 32 * j + tid, nt); st_relaxed32(G.o + 4096 + 32 * j + tid, nt);
                    st_relaxed32(G.ctx + 32 * j + tid, nt); st_relaxed32(G.ctx + 4096 + 32 * j + tid, nt);
                }
            }
            if (tid >= 64 && tid < 72) st_relaxed32((uint32_t*)P.out + 8 * j + (tid - 64), 0);
            mbar_wait(sb + SM_BAR + BAR_W, 0);
            LAND(tid == 0, 17408 + 0 * 128 + j);
            if (tid == 96) {
                mbar_expect_tx(sb + SM_BAR + BAR_W + 8, 32768);
                issue_tall(sb + SM_WQB, &M.m_wqB, j * 32, 0, sb + SM_BAR + BAR_W + 8, pol);
            }
            __syncwarp();
            STAMP(tid == 0, 15);
            uint2 bf[16];
            tall_prep(bf, sb + SM_P, warp, g, t);
            gemv_tall(sb + SM_WQ, bf, (float*)(smem + SM_RED1), warp, g, t);
            tall_finish((float*)(smem + SM_RED1), G.qA + qoff, tid, tag, 0, h >= HCLR ? 32 : 64);
            STAMP(tid == 0, 1);
            tall_prep(bf, sb + SM_P + 2048, warp, g, t);
            mbar_wait(sb + SM_BAR + BAR_W + 8, 0);
            LAND(tid == 0, 17408 + 1 * 128 + j);
            if (tid == 96) {
                mbar_expect_tx(sb + SM_BAR + BAR_W + 16, 32768);
                tma_2d(sb + SM_WUK, &M.m_wuk, h * 128, qd * 128, sb + SM_BAR + BAR_W + 16, pol);
            }
            __syncwarp();
            gemv_tall(sb + SM_WQB, bf, red, warp, g, t);
            tall_finish(red, G.qB + qoff, tid, tag);
            if (tid == 96) mbar_arrive(sb + SM_BAR + BAR_WFREE);
            STAMP(tid == 0, 25);
            named_bar(1, 128);
            uint4 qf[4];
            {
                const float* qp = G.qB + ((g & 1) * 32 + h) * 128 + t * 8;
                uint4 v[8];
                unsigned it = 0;
                while (true) {
                    uint32_t bad = 0;
#pragma unroll
                    for (int i = 0; i < 8; i++) v[i] = ld_relaxed128(qp + (i >> 1) * 32 + (i & 1) * 4);
#pragma unroll
                    for (int i = 0; i < 8; i++) bad |= bad4(v[i], tag);
                    if (!__any_sync(~0u, bad & 1u)) break;
                    __nanosleep(100);
                    if (++it > SPIN_LIMIT) __trap();
                }
#pragma unroll
                for (int s = 0; s < 4; s++)
                    qf[s] = make_uint4(pack_bf16(__uint_as_float(v[2 * s].x), __uint_as_float(v[2 * s].y)),
                                       pack_bf16(__uint_as_float(v[2 * s].z), __uint_as_float(v[2 * s].w)),
                                       pack_bf16(__uint_as_float(v[2 * s + 1].x), __uint_as_float(v[2 * s + 1].y)),
                                       pack_bf16(__uint_as_float(v[2 * s + 1].z), __uint_as_float(v[2 * s + 1].w)));
            }
            mbar_wait(sb + SM_BAR + BAR_W + 16, 0);
            LAND(tid == 0, 17408 + 2 * 128 + j);
#pragma unroll
            for (int jj = 0; jj < 2; jj++) {
                float c[4] = {0.f, 0.f, 0.f, 0.f};
#pragma unroll
                for (int s = 0; s < 4; s++) {
                    const uint32_t a = sb + SM_WUK + (32 * warp + 16 * jj + g) * 256 + (t + 4 * s) * 16;
                    const uint4 u = lds128(a), v = lds128(a + 2048);
                    mma16816(c, u.x, v.x, u.y, v.y, qf[s].x, qf[s].y);
                    mma16816(c, u.z, v.z, u.w, v.w, qf[s].z, qf[s].w);
                }
                const float val = (t & 2) ? ((t & 1) ? c[3] : c[2]) : ((t & 1) ? c[1] : c[0]);
                const int cc = 128 * qd + 32 * warp + 16 * jj + g + ((t & 2) ? 8 : 0);
                const int off = (cc >> 6) * 2048 + h * 64 + ((((cc & 63) >> 3) ^ (h & 7)) << 3) + (cc & 7);
                G.qabs[(t & 1) * 16384 + off] = __float2bfloat16(val);
            }
            named_bar(1, 128);
            if (tid == 0) red_release(&G.cntQabs.v);
            STAMP(tid == 0, 4);
            if (h >= HCLR) {
#pragma unroll
                for (int k = 0; k < 8; k++)
                    st_relaxed128(G.partO + (size_t)((32 + h) * 128 + 16 * k + (tid >> 3)) * 128 + qd * 32 + (tid & 7) * 4, nt, nt, nt, nt);
                if (tid < 64) st_relaxed128((char*)G.partML + ((32 + h) * 128 + qd * 32) * 32 + tid * 16, nt, nt, nt, nt);
                __threadfence();
                tall_finish((float*)(smem + SM_RED1), G.qA + qoff, tid, tag, 32, 64);
            }
        }

        if (isB) {
            const int ib = cta - NA_CTA;
            float acc[8][16];
#pragma unroll
            for (int i = 0; i < 8; i++)
#pragma unroll
                for (int k = 0; k < 16; k++) acc[i][k] = 0.f;
            float mrun[8], lrun[8];
#pragma unroll
            for (int i = 0; i < 8; i++) { mrun[i] = -INFINITY; lrun[i] = 0.f; }
            const uint64_t dQ = make_desc(sb + SM_SLOT + 5 * 32768);
            const uint64_t dP = make_desc(sb + SM_P);
            const uint32_t pst = sb + SM_P + (((lane >> 4) * 8 + (lane & 7)) * 128) + (((2 * warp + ((lane >> 3) & 1)) ^ (lane & 7)) << 4);
            mbar_wait(sb + SM_BAR + BAR_QABS, 0);
            STAMP(tid == 0, 5);
            int s0 = 0; uint32_t ph0 = 0;
            for (int it = 0; it < 16; it++) {
                int s1 = s0 + 1; uint32_t ph1 = ph0;
                if (s1 == 5) { s1 = 0; ph1 ^= 1; }
                const uint64_t dA0 = make_desc(sb + SM_SLOT + s0 * 32768), dA1 = make_desc(sb + SM_SLOT + s1 * 32768);
                float S[16];
                mbar_wait(sb + SM_BAR + BAR_BFULL + s0 * 8, ph0);
                mbar_wait(sb + SM_BAR + BAR_BFULL + s1 * 8, ph1);
                wg_fence();
#pragma unroll
                for (int k = 0; k < 32; k++) {
                    const uint64_t da = ((k < 16) ? dA0 : dA1) + (uint64_t)((((k >> 2) & 3) * 8192 + (k & 3) * 32) >> 4);
                    const uint64_t db = dQ + (uint64_t)(((k >> 2) * 4096 + (k & 3) * 32) >> 4);
                    wgmma_n32<0>(S, da, db, k > 0);
                }
                wg_commit();
                wg_wait<0>();
#pragma unroll
                for (int i = 0; i < 16; i++) S[i] *= SCALE;
                float mx[8];
#pragma unroll
                for (int i = 0; i < 8; i++) {
                    mx[i] = fmaxf(S[4 * (i >> 1) + (i & 1)], S[4 * (i >> 1) + 2 + (i & 1)]);
                    mx[i] = fmaxf(mx[i], __shfl_xor_sync(~0u, mx[i], 4));
                    mx[i] = fmaxf(mx[i], __shfl_xor_sync(~0u, mx[i], 8));
                    mx[i] = fmaxf(mx[i], __shfl_xor_sync(~0u, mx[i], 16));
                }
                if (g == 0) {
#pragma unroll
                    for (int jb = 0; jb < 4; jb++)
                        *(float2*)(red + warp * 32 + 8 * jb + 2 * t) = make_float2(mx[2 * jb], mx[2 * jb + 1]);
                }
                named_bar(1, 128);
                float al[8];
                bool chg = false;
                uint32_t R[8];
#pragma unroll
                for (int jb = 0; jb < 4; jb++) {
                    float2 a = *(float2*)(red + 8 * jb + 2 * t), b = *(float2*)(red + 32 + 8 * jb + 2 * t);
                    float2 c = *(float2*)(red + 64 + 8 * jb + 2 * t), d = *(float2*)(red + 96 + 8 * jb + 2 * t);
                    const float n0 = fmaxf(mrun[2 * jb], fmaxf(fmaxf(a.x, b.x), fmaxf(c.x, d.x)) * LOG2E);
                    const float n1 = fmaxf(mrun[2 * jb + 1], fmaxf(fmaxf(a.y, b.y), fmaxf(c.y, d.y)) * LOG2E);
                    chg |= (n0 != mrun[2 * jb]) | (n1 != mrun[2 * jb + 1]);
                    al[2 * jb] = ex2(mrun[2 * jb] - n0);
                    al[2 * jb + 1] = ex2(mrun[2 * jb + 1] - n1);
                    mrun[2 * jb] = n0; mrun[2 * jb + 1] = n1;
                    R[2 * jb]     = pack_bf16(ex2(fmaf(S[4 * jb], LOG2E, -n0)), ex2(fmaf(S[4 * jb + 1], LOG2E, -n1)));
                    R[2 * jb + 1] = pack_bf16(ex2(fmaf(S[4 * jb + 2], LOG2E, -n0)), ex2(fmaf(S[4 * jb + 3], LOG2E, -n1)));
                    lrun[2 * jb]     = fmaf(lrun[2 * jb], al[2 * jb], bf_lo(R[2 * jb]) + bf_lo(R[2 * jb + 1]));
                    lrun[2 * jb + 1] = fmaf(lrun[2 * jb + 1], al[2 * jb + 1], bf_hi(R[2 * jb]) + bf_hi(R[2 * jb + 1]));
                }
                asm volatile("stmatrix.sync.aligned.m8n8.x4.trans.shared.b16 [%0], {%1,%2,%3,%4};"
                             ::"r"(pst), "r"(R[0]), "r"(R[1]), "r"(R[2]), "r"(R[3]) : "memory");
                asm volatile("stmatrix.sync.aligned.m8n8.x4.trans.shared.b16 [%0], {%1,%2,%3,%4};"
                             ::"r"(pst + 2048), "r"(R[4]), "r"(R[5]), "r"(R[6]), "r"(R[7]) : "memory");
                asm volatile("fence.proxy.async.shared::cta;" ::: "memory");
                if (__any_sync(~0u, chg)) {
#pragma unroll
                    for (int mt = 0; mt < 8; mt++)
#pragma unroll
                        for (int k = 0; k < 16; k++) acc[mt][k] *= al[2 * (k >> 2) + (k & 1)];
                }
                named_bar(1, 128);
                wg_fence();
#pragma unroll
                for (int mt = 0; mt < 4; mt++)
#pragma unroll
                    for (int kk = 0; kk < 4; kk++)
                        wgmma_n32<1>(acc[mt], dA0 + (uint64_t)((mt * 8192 + kk * 2048) >> 4), dP + (uint64_t)((kk * 32) >> 4), 1);
                wg_commit();
#pragma unroll
                for (int mt = 0; mt < 4; mt++)
#pragma unroll
                    for (int kk = 0; kk < 4; kk++)
                        wgmma_n32<1>(acc[4 + mt], dA1 + (uint64_t)((mt * 8192 + kk * 2048) >> 4), dP + (uint64_t)((kk * 32) >> 4), 1);
                wg_commit();
                wg_wait<1>();
                if (lane == 0) mbar_arrive(sb + SM_BAR + BAR_BEMPTY + s0 * 8);
                wg_wait<0>();
                if (lane == 0) mbar_arrive(sb + SM_BAR + BAR_BEMPTY + s1 * 8);
                s0 = s1 + 1; ph0 = ph1;
                if (s0 == 5) { s0 = 0; ph0 ^= 1; }
            }
#pragma unroll
            for (int i = 0; i < 8; i++) {
                lrun[i] += __shfl_xor_sync(~0u, lrun[i], 4);
                lrun[i] += __shfl_xor_sync(~0u, lrun[i], 8);
                lrun[i] += __shfl_xor_sync(~0u, lrun[i], 16);
            }
            if (g == 0) {
#pragma unroll
                for (int jb = 0; jb < 4; jb++) {
                    *(float2*)(red + 128 + warp * 32 + 8 * jb + 2 * t) = make_float2(lrun[2 * jb], lrun[2 * jb + 1]);
                    if (warp == 0) *(float2*)(red + 256 + 8 * jb + 2 * t) = make_float2(mrun[2 * jb], mrun[2 * jb + 1]);
                }
            }
            named_bar(1, 128);
            if (tid == 0) mbar_arrive(sb + SM_BAR + BAR_BDONE);
            if (tid < 32)
                G.bml[ib * 32 + tid] = make_float2(red[256 + tid], red[128 + tid] + red[160 + tid] + red[192 + tid] + red[224 + tid]);
            float* bp = G.bpart + (size_t)ib * 16384 + (2 * t) * 512 + 16 * warp + g;
#pragma unroll
            for (int mt = 0; mt < 8; mt++)
#pragma unroll
                for (int k = 0; k < 16; k++)
                    bp[(8 * (k >> 2) + (k & 1)) * 512 + 64 * mt + ((k >> 1) & 1) * 8] = acc[mt][k];
            named_bar(1, 128);
            if (tid == 0) red_release(&G.cntB.v);
            STAMP(tid == 0, 6);
        }

        if (hasSlice) {
            if (tid == 0) {
                wait_prog(smem + SM_BAR + W_PROG, TUV);
                wait_counter(&G.cntB.v, (epoch + 1) * NB_CTA, 500);
                if (cta == 0) st_relaxed32(&G.epoch.v, epoch + 1);
                asm volatile("prefetch.tensormap [%0];" ::"l"(&M.m_uv[late]) : "memory");
                asm volatile("prefetch.tensormap [%0];" ::"l"(&M.m_w[mat]) : "memory");
            }
            named_bar(1, 128);
            if (tid == 32) mbar_arrive(sb + SM_BAR + BAR_PDONE);
            STAMP(tid == 0, 7);
            {
                const int b = tid >> 6, cp = tid & 63;
                uint2 ml[8];
#pragma unroll
                for (int i = 0; i < 8; i++) ml[i] = ld_relaxed64(G.bml + (b * 8 + i) * 32 + h);
                uint4 pv[2][8];
#pragma unroll
                for (int i = 0; i < 16; i++)
                    pv[i >> 3][i & 7] = ld_relaxed128(G.bpart + (size_t)(b * 8 + (i & 7)) * 16384 + h * 512 + (i >> 3) * 256 + 4 * cp);
                float M = __uint_as_float(ml[0].x);
#pragma unroll
                for (int i = 1; i < 8; i++) M = fmaxf(M, __uint_as_float(ml[i].x));
                float L = 0.f, wgt[8];
#pragma unroll
                for (int i = 0; i < 8; i++) {
                    wgt[i] = ex2(__uint_as_float(ml[i].x) - M);
                    L = fmaf(wgt[i], __uint_as_float(ml[i].y), L);
                }
                const float inv = 1.f / L;
#pragma unroll
                for (int x = 0; x < 2; x++) {
                    float v0 = 0.f, v1 = 0.f, v2 = 0.f, v3 = 0.f;
#pragma unroll
                    for (int i = 0; i < 8; i++) {
                        v0 = fmaf(wgt[i], __uint_as_float(pv[x][i].x), v0);
                        v1 = fmaf(wgt[i], __uint_as_float(pv[x][i].y), v1);
                        v2 = fmaf(wgt[i], __uint_as_float(pv[x][i].z), v2);
                        v3 = fmaf(wgt[i], __uint_as_float(pv[x][i].w), v3);
                    }
                    *(uint2*)(smem + SM_P + b * 1024 + x * 512 + cp * 8) = make_uint2(pack_bf16(v0 * inv, v1 * inv), pack_bf16(v2 * inv, v3 * inv));
                }
            }
            STAMP(tid == 0, 8);
        }
        {
            named_bar(1, 128);
#pragma unroll 1
            for (uint64_t plan = j < 64 ? 0xF7351260ull : (j < 124 ? (late ? 0xF75314260ull : 0xF7514603ull) : (hasSlice ? 0xF753426ull : 0xF10ull));
                 plan != 0xF; plan >>= 4) {
                const int step = plan & 15;
                if ((step & 14) == 4) {
                    const int hh = rg + 8 * warp;
                    const uint32_t real = step & 1, both = real & (mat | (warp != 3));
                    if (both) wait_ticket(smem + SM_BAR + W_PROG, mat ? NT + YB : min((33 + hh) * 128 + LAGT, NT + YLATE) + YX);
                    __syncwarp();
                    const float* src = (mat ? G.ctx : G.o) + hh * 128 + lane * 4;
                    uint4 v[2];
                    v[0] = v[1] = make_uint4(tag, tag, tag, tag);
                    uint32_t bad0 = real, bad1 = both;
                    unsigned it = 0;
                    while (true) {
                        ld_relaxed128_if(v[0], src, bad0);
                        ld_relaxed128_if(v[1], src + 4096, bad1);
                        bad0 = bad4(v[0], tag) & 1u; bad1 = bad4(v[1], tag) & 1u;
                        if (!__any_sync(~0u, bad0 | bad1)) break;
                        if (++it > SPIN_LIMIT) __trap();
                    }
#pragma unroll
                    for (int b = 0; b < 2; b++)
                        *(uint2*)(smem + SM_VEC + V_X + b * XSTR + (128 * warp + 4 * lane) * 2) =
                            make_uint2(pack_bf16(__uint_as_float(v[b].x), __uint_as_float(v[b].y)), pack_bf16(__uint_as_float(v[b].z), __uint_as_float(v[b].w)));
                    named_bar(1, 128);
                    STAMP(tid == 0, 29);
                } else if (step >= 6) {
                    const uint32_t real = step & 1;
                    const uint32_t xa = sb + SM_VEC + V_X + (lane & 1) * XSTR + 8 * (lane >> 3) * 2;
                    const uint32_t wa = sb + SM_SQ + 2 * 16384 + (8 * (lane >> 4) + (lane & 7)) * 128 +
                                        (((2 * warp + ((lane >> 3) & 1)) ^ (lane & 7)) << 4);
                    const uint32_t bs = sb + SM_BAR + BAR_S + 16;
                    const float* src = G.o + 4096 + (24 + rg) * 128 + lane * 4;
                    const uint32_t needx = real & (mat ^ 1);
                    uint32_t* dst = (uint32_t*)P.out + (t & 1) * 512 + mat * 256 + cg * 32 + warp * 8 + (t >> 1) * 4 + (g >> 1);
                    asm volatile("" : "+l"(dst));
                    uint4 v = make_uint4(tag, tag, tag, tag);
                    float d[4][4];
#pragma unroll
                    for (int i = 0; i < 16; i++) (&d[0][0])[i] = 0.f;
#pragma unroll 1
                    for (int u = 0; u < 3; u++) {
                        uint4 xf[4];
                        if (needx && u == XU) wait_ticket(smem + SM_BAR + W_PROG, NT + YP + (rg - 7) * YPS);
                        __syncwarp();
                        ld_relaxed128_if(v, src, needx & (u == XU));
#pragma unroll
                        for (int i = 0; i < 4; i++) xf[i] = ldsm4(xa + u * 256 + i * 64);
                        if (real) mbar_wait_nt(bs + u * 8, 0);
#pragma unroll
                        for (int i = 0; i < 4; i++) {
                            const uint4 w0 = ldsm4t(wa + u * 16384 + i * 4096), w1 = ldsm4t(wa + u * 16384 + i * 4096 + 2048);
                            mma16816(d[(i & 1) * 2], w0.x, w0.y, w0.z, w0.w, xf[i].x, xf[i].y);
                            mma16816(d[(i & 1) * 2 + 1], w1.x, w1.y, w1.z, w1.w, xf[i].z, xf[i].w);
                        }
                    }
                    unsigned it = 0;
                    while (__any_sync(~0u, bad4(v, tag) & 1u)) {
                        if (++it > SPIN_LIMIT) __trap();
                        v = ld_relaxed128(src);
                    }
                    STAMP(tid == 96, 20);
                    if (!mat)
                        *(uint2*)(smem + SM_VEC + V_X + XSTR + (384 + 4 * lane) * 2) =
                            make_uint2(pack_bf16(__uint_as_float(v.x), __uint_as_float(v.y)), pack_bf16(__uint_as_float(v.z), __uint_as_float(v.w)));
                    __syncwarp();
                    uint4 xf[4], w[8];
#pragma unroll
                    for (int i = 0; i < 4; i++) xf[i] = ldsm4(xa + 3 * 256 + i * 64);
                    if (real) mbar_wait_nt(bs + 24, 0);
#pragma unroll
                    for (int i = 0; i < 2 * RA; i++) w[i] = ldsm4t(wa + 3 * 16384 + i * 2048);
#pragma unroll
                    for (int i = 0; i < RA; i++) {
                        mma16816(d[(i & 1) * 2], w[2 * i].x, w[2 * i].y, w[2 * i].z, w[2 * i].w, xf[i].x, xf[i].y);
                        mma16816(d[(i & 1) * 2 + 1], w[2 * i + 1].x, w[2 * i + 1].y, w[2 * i + 1].z, w[2 * i + 1].w, xf[i].z, xf[i].w);
                    }
                    if (RA < 4) {
#pragma unroll
                        for (int i = 0; i < 4; i++) {
                            d[0][i] = (d[0][i] + d[1][i]) + (d[2][i] + d[3][i]);
                            d[1][i] = d[2][i] = d[3][i] = 0.f;
                            asm volatile("" : "+f"(d[0][i]));
                        }
                        if (real) mbar_wait_nt(bs + 32, 0);
#pragma unroll
                        for (int i = 2 * RA; i < 8; i++) w[i] = ldsm4t(wa + 3 * 16384 + i * 2048);
#pragma unroll
                        for (int i = RA; i < 4; i++) {
                            mma16816(d[(i - RA) * 2], w[2 * i].x, w[2 * i].y, w[2 * i].z, w[2 * i].w, xf[i].x, xf[i].y);
                            mma16816(d[(i - RA) * 2 + 1], w[2 * i + 1].x, w[2 * i + 1].y, w[2 * i + 1].z, w[2 * i + 1].w, xf[i].z, xf[i].w);
                        }
                    }
                    STAMP(tid == 64, 22);
                    float e[4];
#pragma unroll
                    for (int i = 0; i < 4; i++) e[i] = (t & 2) ? ((t & 1) ? d[i][3] : d[i][2]) : ((t & 1) ? d[i][1] : d[i][0]);
                    red_out(dst, RA == 3 ? e[0] + e[1] : (e[0] + e[1]) + (e[2] + e[3]), g, real);
                    STAMP(tid == 64, 13);
                } else if (step >= 2) {
                    uint2 bf[16];
                    tall_prep(bf, sb + SM_P, warp, g, t);
                    if (step & 1) mbar_wait(sb + SM_BAR + BAR_S + (warp >> 1) * 8, 0);
                    LAND(tid == 64, 17408 + 3 * 128 + j);
                    gemv_tall(sb + SM_SQ, bf, red + 512, warp, g, t);
                    tall_finish(red + 512, G.ctx + ((tid >> 5) & 1) * 4096 + 32 * j + (tid & 31), tid, tag, 0, (step & 1) ? 64 : 0);
                    STAMP(tid == 0, 12);
                } else {
                    const int b = step;
                    const int hm = min(h, 31), bh = 32 * b + hm;
                    wait_ticket(smem + SM_BAR + W_PROG, min((bh + 1) * 128 + LAGT, NT + YLATE + max(hm - 27, 0) * YSL));
                    __syncwarp();
                    float* rb = red + b * 256;
                    combineA(G, bh, qd, tag, rb, tid, smem + SM_BAR + W_PROG);
                    {
                        if (tid < 32)
                            st_relaxed32(G.o + bh * 128 + 32 * qd + tid, tagw((rb[tid] + rb[32 + tid]) + (rb[64 + tid] + rb[96 + tid]), tag));
                        STAMP(tid == 0, 9 + 2 * b);
                    }
                }
            }
        }
    }
}

typedef CUresult (*EncodeFn)(CUtensorMap*, CUtensorMapDataType, cuuint32_t, void*, const cuuint64_t*, const cuuint64_t*,
                             const cuuint32_t*, const cuuint32_t*, CUtensorMapInterleave, CUtensorMapSwizzle,
                             CUtensorMapL2promotion, CUtensorMapFloatOOBfill);

}

extern "C" void kernel_launch(void* const* d_in, const int* in_sizes, int n_in, void* d_out, int out_size) {
    (void)in_sizes; (void)n_in; (void)out_size;
    static EncodeFn encode = nullptr;
    static void* scratch = nullptr;
    if (!encode) {
        void* fn = nullptr;
        cudaDriverEntryPointQueryResult st;
        cudaGetDriverEntryPoint("cuTensorMapEncodeTiled", &fn, cudaEnableDefault, &st);
        encode = (EncodeFn)fn;
        cudaGetSymbolAddress(&scratch, g_raw);
        cudaFuncSetAttribute(fused_decode_kernel, cudaFuncAttributeMaxDynamicSharedMemorySize, SM_TOTAL);
    }
    Ptrs P;
    Maps M;
    auto mk = [&](CUtensorMap* m, void* ptr, cuuint64_t cols, cuuint64_t rows, cuuint32_t bc, cuuint32_t br, CUtensorMapSwizzle sw,
                  CUtensorMapL2promotion promo) {
        const cuuint64_t gdim[2] = {cols, rows};
        const cuuint64_t gstr[1] = {cols * 2};
        const cuuint32_t box[2] = {bc, br};
        const cuuint32_t estr[2] = {1, 1};
        encode(m, CU_TENSOR_MAP_DATA_TYPE_BFLOAT16, 2, ptr, gdim, gstr, box, estr, CU_TENSOR_MAP_INTERLEAVE_NONE, sw,
               promo, CU_TENSOR_MAP_FLOAT_OOB_FILL_NONE);
    };
    mk(&M.m_wq, d_in[3], 4096, 512, 32, 256, CU_TENSOR_MAP_SWIZZLE_64B, CU_TENSOR_MAP_L2_PROMOTION_NONE);
    auto mk3 = [&](CUtensorMap* m, void* ptr, cuuint64_t cols, cuuint64_t rows, cuuint32_t br, cuuint32_t bb) {
        const cuuint64_t gdim[3] = {64, rows, cols / 64};
        const cuuint64_t gstr[2] = {cols * 2, 128};
        const cuuint32_t box[3] = {64, br, bb};
        const cuuint32_t estr[3] = {1, 1, 1};
        encode(m, CU_TENSOR_MAP_DATA_TYPE_BFLOAT16, 3, ptr, gdim, gstr, box, estr, CU_TENSOR_MAP_INTERLEAVE_NONE,
               CU_TENSOR_MAP_SWIZZLE_128B, CU_TENSOR_MAP_L2_PROMOTION_L2_256B, CU_TENSOR_MAP_FLOAT_OOB_FILL_NONE);
    };
    mk3(&M.m_v, d_in[2], 128, 524288, 64, 2);
    mk(&M.m_uv[0], d_in[9], 4096, 512, 32, PV, CU_TENSOR_MAP_SWIZZLE_64B, CU_TENSOR_MAP_L2_PROMOTION_NONE);
    mk(&M.m_uv[1], d_in[9], 4096, 512, 32, PV, CU_TENSOR_MAP_SWIZZLE_64B, (CUtensorMapL2promotion)VPROMO);
    mk(&M.m_w[0], d_in[4], 512, 4096, 64, PR, CU_TENSOR_MAP_SWIZZLE_128B, (CUtensorMapL2promotion)WPROMO);
    mk(&M.m_w[1], d_in[10], 512, 4096, 64, PR, CU_TENSOR_MAP_SWIZZLE_128B, (CUtensorMapL2promotion)WPROMO);
    mk(&M.m_ckv, d_in[6], 512, 16384, 64, 64, CU_TENSOR_MAP_SWIZZLE_128B, CU_TENSOR_MAP_L2_PROMOTION_L2_256B);
    mk(&M.m_wqB, d_in[7], 4096, 512, 32, 256, CU_TENSOR_MAP_SWIZZLE_64B, CU_TENSOR_MAP_L2_PROMOTION_NONE);
    mk(&M.m_wuk, d_in[8], 4096, 512, 128, 128, CU_TENSOR_MAP_SWIZZLE_NONE, CU_TENSOR_MAP_L2_PROMOTION_L2_256B);
    P.xA = (const __nv_bfloat16*)d_in[0];
    P.K = (const __nv_bfloat16*)d_in[1];
    P.xB = (const __nv_bfloat16*)d_in[5];
    P.out = (__nv_bfloat16*)d_out;
    P.g = (Scratch*)scratch;
    cudaLaunchConfig_t cfg = {};
    cfg.gridDim = dim3(GRID);
    cfg.blockDim = dim3(NTHREADS);
    cfg.dynamicSmemBytes = SM_TOTAL;
    cfg.stream = cudaStreamPerThread;
    cudaLaunchAttribute attr;
    attr.id = cudaLaunchAttributeCooperative;
    attr.val.cooperative = 1;
    cfg.attrs = &attr;
    cfg.numAttrs = 1;
    cudaLaunchKernelEx(&cfg, fused_decode_kernel, P, M);
}
```

```cpp
#include <cuda_runtime.h>
#include <cuda_bf16.h>
#include <cuda.h>
#include <stdint.h>

namespace {

constexpr int NT       = 8192;
constexpr int GRID     = 132;
constexpr int NB_CTA   = 16;
constexpr int NA_CTA   = GRID - NB_CTA;
constexpr int NWORK    = 3;
#define YV 290
#define DV 56
#define JE0 112
#define VPROMO CU_TENSOR_MAP_L2_PROMOTION_L2_256B
#define YB 582
#define YW 407
#define DW 68
#define YX 150
#define YP 605
#define YPS 0
#define XU 2
#define RA 2
#define PR 64
#define PV 128
#define DL 6
#define WPROMO CU_TENSOR_MAP_L2_PROMOTION_L2_256B
#define XRV 330
#define TV 3200
#define PFB 8192
#define LAGT 1060
#define YLATE 120
#define YSL 70
#define YO 450
#define YOS 40
#define TUV (43 * 128)
#define XPK 80
#define FRZ 60
#define QDELAY 500
constexpr int NEARX = 400;
constexpr int HCLR  = 26;
constexpr int BINFL = 2;
constexpr int NSTATIC  = NA_CTA * NWORK;
constexpr unsigned DRAWS = (NT - NSTATIC) + GRID * NWORK;
static_assert(52 * 128 + LAGT + 300 <= NT && TUV + 10 * 128 <= NT, "wait_prog thresholds must be reachable");
constexpr int NTHREADS = 256;
constexpr float SCALE = 0.08838834764831845f, LOG2E = 1.4426950408889634f;
constexpr unsigned SPIN_LIMIT = 1u << 22;

constexpr int SM_SLOT  = 0;
constexpr int SM_QA    = 196608;
constexpr int SM_P     = SM_QA + 16384;
constexpr int SM_RED1  = SM_P + 4096;
constexpr int SM_RED2  = SM_RED1 + 2048;
constexpr int SM_VEC   = SM_RED2 + 4096;
constexpr int SM_BAR   = SM_VEC + 3072;
constexpr int SM_TOTAL = SM_BAR + 352;
constexpr int V_X    = 512;
constexpr int BAR_FULL = 0;
constexpr int BAR_PDONE= 48;
constexpr int BAR_BDONE= 56;
constexpr int BAR_QABS = 72;
constexpr int BAR_BFULL= 80;
constexpr int BAR_BEMPTY=120;
constexpr int BAR_WFREE= 160;
constexpr int BAR_W    = 168;
constexpr int BAR_S    = 192;
constexpr int BAR_Q    = 264;
constexpr int W_EPOCH  = 328;
constexpr int W_PROG   = 336;
constexpr int SM_WQ = 3 * 32768, SM_WQB = 4 * 32768, SM_WUK = 5 * 32768;
constexpr int SM_SQ = 3 * 32768;
constexpr int XSTR = 1024 + 16;

struct __align__(128) Cnt { unsigned v; unsigned pad[31]; };
struct __align__(128) Scratch {
    Cnt epoch, ticket, cntQabs, cntB;
    float qA[64 * 128], qB[64 * 128];
    __nv_bfloat16 qabs[2 * 32 * 512];
    float  partO[NT * 128];
    float2 partML[NT * 4];
    float  bpart[NB_CTA * 32 * 512];
    float2 bml[NB_CTA * 32];
    float  ctx[32 * 4 * 2 * 128];
    float  o[2 * 4096];
};
__device__ __align__(128) unsigned char g_raw[sizeof(Scratch)];

__device__ __forceinline__ int slice_of(int cta) {
    const int r = (cta >> 2) & 3, s = cta >> 4;
    const int grp = (r & 1) ? (r == 1 ? s : (s >> 1) + ((s & 1) ? 8 : 28)) : 12 + 4 * r + s;
    return cta >= 128 ? cta : 4 * grp + (cta & 3);
}

#define STAMP(cond, i) do {} while (0)
#define LAND(cond, i) do {} while (0)

__device__ __forceinline__ void mbar_init(uint32_t bar, int cnt) {
    asm volatile("mbarrier.init.shared::cta.b64 [%0], %1;" ::"r"(bar), "r"(cnt) : "memory");
}
__device__ __forceinline__ void mbar_expect_tx(uint32_t bar, uint32_t bytes) {
    asm volatile("mbarrier.arrive.expect_tx.shared::cta.b64 _, [%0], %1;" ::"r"(bar), "r"(bytes) : "memory");
}
__device__ __forceinline__ void mbar_arrive(uint32_t bar) {
    asm volatile("mbarrier.arrive.shared::cta.b64 _, [%0];" ::"r"(bar) : "memory");
}
__device__ __forceinline__ void mbar_wait(uint32_t bar, uint32_t parity) {
    unsigned it = 0;
    while (true) {
        uint32_t ok;
        asm volatile("{\n.reg .pred p;\nmbarrier.try_wait.parity.shared::cta.b64 p, [%1], %2;\nselp.u32 %0, 1, 0, p;\n}\n"
                     : "=r"(ok) : "r"(bar), "r"(parity) : "memory");
        if (ok) break;
        if (++it > SPIN_LIMIT) __trap();
    }
}
__device__ __forceinline__ void mbar_wait_nt(uint32_t bar, uint32_t parity) {
#pragma unroll 1
    for (unsigned it = 0; it < SPIN_LIMIT; it++) {
        uint32_t ok;
        asm volatile("{\n.reg .pred p;\nmbarrier.try_wait.parity.shared::cta.b64 p, [%1], %2;\nselp.u32 %0, 1, 0, p;\n}\n"
                     : "=r"(ok) : "r"(bar), "r"(parity) : "memory");
        if (ok) break;
    }
}
__device__ __forceinline__ bool mbar_test(uint32_t bar, uint32_t parity) {
    uint32_t ok;
    asm volatile("{\n.reg .pred p;\nmbarrier.test_wait.parity.shared::cta.b64 p, [%1], %2;\nselp.u32 %0, 1, 0, p;\n}\n"
                 : "=r"(ok) : "r"(bar), "r"(parity) : "memory");
    return ok;
}
__device__ __forceinline__ void bulk_load(uint32_t dst, const void* src, uint32_t bytes, uint32_t bar, uint64_t pol) {
    asm volatile("cp.async.bulk.shared::cluster.global.mbarrier::complete_tx::bytes.L2::cache_hint [%0], [%1], %2, [%3], %4;"
                 ::"r"(dst), "l"(src), "r"(bytes), "r"(bar), "l"(pol) : "memory");
}
__device__ __forceinline__ void bulk_load_nohint(uint32_t dst, const void* src, uint32_t bytes, uint32_t bar) {
    asm volatile("cp.async.bulk.shared::cluster.global.mbarrier::complete_tx::bytes [%0], [%1], %2, [%3];"
                 ::"r"(dst), "l"(src), "r"(bytes), "r"(bar) : "memory");
}
__device__ __forceinline__ void tma_2d(uint32_t dst, const CUtensorMap* map, int c0, int c1, uint32_t bar, uint64_t pol) {
    asm volatile("cp.async.bulk.tensor.2d.shared::cluster.global.mbarrier::complete_tx::bytes.L2::cache_hint [%0], [%1, {%3, %4}], [%2], %5;"
                 ::"r"(dst), "l"(map), "r"(bar), "r"(c0), "r"(c1), "l"(pol) : "memory");
}
__device__ __forceinline__ void tma_3d(uint32_t dst, const CUtensorMap* map, int c1, int c2, uint32_t bar, uint64_t pol) {
    asm volatile("cp.async.bulk.tensor.3d.shared::cluster.global.mbarrier::complete_tx::bytes.L2::cache_hint [%0], [%1, {%3, %4, %5}], [%2], %6;"
                 ::"r"(dst), "l"(map), "r"(bar), "r"(0), "r"(c1), "r"(c2), "l"(pol) : "memory");
}
__device__ __forceinline__ void wait_prog(const unsigned char* smem_word, unsigned th) {
    unsigned it = 0;
    while (*(volatile const unsigned*)(smem_word + 8) + NSTATIC < th) {
        __nanosleep(60);
        if (++it > SPIN_LIMIT) __trap();
    }
}
__device__ __forceinline__ uint32_t now_ns() {
    uint32_t t;
    asm volatile("mov.u32 %0, %globaltimer_lo;" : "=r"(t) :: "memory");
    return t;
}
__device__ __forceinline__ void note_draw(unsigned char* smem_word, unsigned raw) {
    const uint32_t a = (uint32_t)__cvta_generic_to_shared(smem_word);
    asm volatile("st.volatile.u32 [%0], %1;" ::"l"(smem_word + 8), "r"(raw) : "memory");
    const uint32_t now = now_ns();
    if ((int)raw < NT - NSTATIC - FRZ) asm volatile("st.volatile.shared.v2.u32 [%0], {%1, %2};" ::"r"(a), "r"(raw), "r"(now) : "memory");
}
__device__ __forceinline__ void wait_ticket(const unsigned char* smem_word, int th) {
    wait_prog(smem_word, min(th, NT - NEARX));
    uint32_t tk, t0;
#pragma unroll 1
    for (unsigned it = 0; it < SPIN_LIMIT; it++) {
        asm volatile("ld.volatile.shared.v2.u32 {%0, %1}, [%2];" : "=r"(tk), "=r"(t0) : "r"((uint32_t)__cvta_generic_to_shared(smem_word)) : "memory");
        if ((int)(now_ns() - t0) >= (th - NSTATIC - (int)tk) * 10) break;
        __nanosleep(20);
    }
}
__device__ __forceinline__ bool mbar_wait_for(uint32_t bar, uint32_t parity, int n) {
    uint32_t c0, c;
    asm volatile("mov.u32 %0, %%clock;" : "=r"(c0) :: "memory");
    do {
        if (mbar_test(bar, parity)) return true;
        asm volatile("mov.u32 %0, %%clock;" : "=r"(c) :: "memory");
    } while ((int)(c - c0) < n);
    return false;
}
__device__ __forceinline__ bool elect_one() {
    uint32_t p;
    asm volatile("{\n.reg .pred p;\nelect.sync _|p, 0xffffffff;\nselp.u32 %0, 1, 0, p;\n}\n" : "=r"(p));
    return p;
}
__device__ __forceinline__ void fence_proxy_async() { asm volatile("fence.proxy.async;" ::: "memory"); }
__device__ __forceinline__ void named_bar(int id, int n) { asm volatile("bar.sync %0, %1;" ::"r"(id), "r"(n) : "memory"); }

__device__ __forceinline__ uint4 lds128(uint32_t a) {
    uint4 v;
    asm volatile("ld.shared.v4.u32 {%0,%1,%2,%3}, [%4];" : "=r"(v.x), "=r"(v.y), "=r"(v.z), "=r"(v.w) : "r"(a));
    return v;
}
__device__ __forceinline__ uint4 ldsm4(uint32_t a) {
    uint4 v;
    asm volatile("ldmatrix.sync.aligned.m8n8.x4.shared.b16 {%0,%1,%2,%3}, [%4];" : "=r"(v.x), "=r"(v.y), "=r"(v.z), "=r"(v.w) : "r"(a));
    return v;
}
__device__ __forceinline__ uint4 ldsm4t(uint32_t a) {
    uint4 v;
    asm volatile("ldmatrix.sync.aligned.m8n8.x4.trans.shared.b16 {%0,%1,%2,%3}, [%4];" : "=r"(v.x), "=r"(v.y), "=r"(v.z), "=r"(v.w) : "r"(a));
    return v;
}
__device__ __forceinline__ uint2 lds64(uint32_t a) {
    uint2 v;
    asm volatile("ld.shared.v2.u32 {%0,%1}, [%2];" : "=r"(v.x), "=r"(v.y) : "r"(a));
    return v;
}
__device__ __forceinline__ uint4 ld_relaxed128(const void* p) {
    uint4 v;
    asm volatile("ld.relaxed.gpu.global.v4.u32 {%0,%1,%2,%3}, [%4];" : "=r"(v.x), "=r"(v.y), "=r"(v.z), "=r"(v.w) : "l"(p) : "memory");
    return v;
}
__device__ __forceinline__ uint2 ld_relaxed64(const void* p) {
    uint2 v;
    asm volatile("ld.relaxed.gpu.global.v2.u32 {%0,%1}, [%2];" : "=r"(v.x), "=r"(v.y) : "l"(p) : "memory");
    return v;
}
__device__ __forceinline__ uint32_t ld_relaxed32(const void* p) {
    uint32_t v;
    asm volatile("ld.relaxed.gpu.global.u32 %0, [%1];" : "=r"(v) : "l"(p) : "memory");
    return v;
}
__device__ __forceinline__ uint32_t ld_acquire32(const void* p) {
    uint32_t v;
    asm volatile("ld.acquire.gpu.global.u32 %0, [%1];" : "=r"(v) : "l"(p) : "memory");
    return v;
}
__device__ __forceinline__ void st_relaxed128(void* p, uint32_t a, uint32_t b, uint32_t c, uint32_t d) {
    asm volatile("st.relaxed.gpu.global.v4.u32 [%0], {%1,%2,%3,%4};" ::"l"(p), "r"(a), "r"(b), "r"(c), "r"(d) : "memory");
}
__device__ __forceinline__ void st_relaxed64(void* p, uint32_t a, uint32_t b) {
    asm volatile("st.relaxed.gpu.global.v2.u32 [%0], {%1,%2};" ::"l"(p), "r"(a), "r"(b) : "memory");
}
__device__ __forceinline__ void red_release(unsigned* p) {
    asm volatile("red.release.gpu.global.add.u32 [%0], 1;" ::"l"(p) : "memory");
}
__device__ __forceinline__ void wait_counter(const unsigned* p, unsigned target, unsigned ns) {
    unsigned it = 0;
    while ((int)(ld_acquire32(p) - target) < 0) {
        __nanosleep(ns);
        if (++it > SPIN_LIMIT) __trap();
    }
}
__device__ __forceinline__ uint32_t prmt(uint32_t a, uint32_t b, uint32_t s) {
    uint32_t d;
    asm("prmt.b32 %0, %1, %2, %3;" : "=r"(d) : "r"(a), "r"(b), "r"(s));
    return d;
}
__device__ __forceinline__ uint32_t pack_bf16(float lo, float hi) {
    uint32_t d;
    asm("cvt.rn.bf16x2.f32 %0, %1, %2;" : "=r"(d) : "f"(hi), "f"(lo));
    return d;
}
__device__ __forceinline__ float ex2(float x) {
    float y;
    asm("ex2.approx.ftz.f32 %0, %1;" : "=f"(y) : "f"(x));
    return y;
}
__device__ __forceinline__ float bf_lo(uint32_t v) { return __uint_as_float(v << 16); }
__device__ __forceinline__ float bf_hi(uint32_t v) { return __uint_as_float(v & 0xffff0000u); }
__device__ __forceinline__ void scale_scores(float& a, float& b) {
    uint32_t p = pack_bf16(a, b);
    p = pack_bf16(bf_lo(p) * SCALE, bf_hi(p) * SCALE);
    a = bf_lo(p); b = bf_hi(p);
}
__device__ __forceinline__ uint32_t tagw(float v, uint32_t tag) {
    uint32_t d;
    asm("lop3.b32 %0, %1, 0xfffffffe, %2, 0xEA;" : "=r"(d) : "r"(__float_as_uint(v)), "r"(tag));
    return d;
}
__device__ __forceinline__ uint32_t bad2(uint32_t x, uint32_t y, uint32_t tag) {
    uint32_t d;
    asm("lop3.b32 %0, %1, %2, %3, 0x7E;" : "=r"(d) : "r"(x), "r"(y), "r"(tag));
    return d;
}
__device__ __forceinline__ uint32_t bad4(const uint4& v, uint32_t tag) { return bad2(v.x, v.y, tag) | bad2(v.z, v.w, tag); }
__device__ __forceinline__ void ld_relaxed128_if(uint4& v, const void* p, uint32_t c) {
    asm volatile("{\n.reg .pred p;\nsetp.ne.u32 p, %5, 0;\n@p ld.relaxed.gpu.global.v4.u32 {%0,%1,%2,%3}, [%4];\n}\n"
                 : "+r"(v.x), "+r"(v.y), "+r"(v.z), "+r"(v.w) : "l"(p), "r"(c) : "memory");
}
__device__ __forceinline__ void ld_relaxed64_if(uint2& v, const void* p, uint32_t c) {
    asm volatile("{\n.reg .pred p;\nsetp.ne.u32 p, %3, 0;\n@p ld.relaxed.gpu.global.v2.u32 {%0,%1}, [%2];\n}\n"
                 : "+r"(v.x), "+r"(v.y) : "l"(p), "r"(c) : "memory");
}
__device__ __forceinline__ void st_relaxed32(void* p, uint32_t a) {
    asm volatile("st.relaxed.gpu.global.u32 [%0], %1;" ::"l"(p), "r"(a) : "memory");
}
__device__ __forceinline__ void red_out(uint32_t* word, float v, int col, uint32_t go) {
    const uint32_t pk = (col & 1) ? pack_bf16(-0.f, v) : pack_bf16(v, -0.f);
    asm volatile("{\n.reg .pred p;\nsetp.ne.u32 p, %2, 0;\n@p red.relaxed.gpu.global.add.noftz.bf16x2 [%0], %1;\n}\n"
                 ::"l"(word), "r"(pk), "r"(go) : "memory");
}
__device__ __forceinline__ void mma16816(float (&c)[4], uint32_t a0, uint32_t a1, uint32_t a2, uint32_t a3,
                                         uint32_t b0, uint32_t b1) {
    asm("mma.sync.aligned.m16n8k16.row.col.f32.bf16.bf16.f32 {%0,%1,%2,%3}, {%4,%5,%6,%7}, {%8,%9}, {%0,%1,%2,%3};"
        : "+f"(c[0]), "+f"(c[1]), "+f"(c[2]), "+f"(c[3])
        : "r"(a0), "r"(a1), "r"(a2), "r"(a3), "r"(b0), "r"(b1));
}
__device__ __forceinline__ uint64_t make_desc(uint32_t addr) {
    return (uint64_t)((addr & 0x3FFFF) >> 4) | ((uint64_t)1 << 16) | ((uint64_t)64 << 32) | ((uint64_t)1 << 62);
}
template <int TRANS_A>
__device__ __forceinline__ void wgmma_n32(float (&d)[16], uint64_t da, uint64_t db, int scale_d) {
    asm volatile("{\n.reg .pred p;\nsetp.ne.b32 p, %18, 0;\n"
                 "wgmma.mma_async.sync.aligned.m64n32k16.f32.bf16.bf16 "
                 "{%0,%1,%2,%3,%4,%5,%6,%7,%8,%9,%10,%11,%12,%13,%14,%15}, %16, %17, p, 1, 1, %19, 0;\n}\n"
                 : "+f"(d[0]), "+f"(d[1]), "+f"(d[2]), "+f"(d[3]), "+f"(d[4]), "+f"(d[5]), "+f"(d[6]), "+f"(d[7]),
                   "+f"(d[8]), "+f"(d[9]), "+f"(d[10]), "+f"(d[11]), "+f"(d[12]), "+f"(d[13]), "+f"(d[14]), "+f"(d[15])
                 : "l"(da), "l"(db), "r"(scale_d), "n"(TRANS_A));
}
__device__ __forceinline__ void wg_fence()  { asm volatile("wgmma.fence.sync.aligned;" ::: "memory"); }
__device__ __forceinline__ void wg_commit() { asm volatile("wgmma.commit_group.sync.aligned;" ::: "memory"); }
template <int N> __device__ __forceinline__ void wg_wait() { asm volatile("wgmma.wait_group.sync.aligned %0;" ::"n"(N) : "memory"); }

__device__ __forceinline__ void issue_tall(uint32_t dst, const CUtensorMap* map, int col, int row, uint32_t bar, uint64_t pol) {
    tma_2d(dst, map, col, row, bar, pol);
    tma_2d(dst + 16384, map, col, row + 256, bar, pol);
}
__device__ __forceinline__ void tall_prep(uint2 (&bf)[16], uint32_t xbase, int w4, int g, int t) {
    const uint32_t xp = xbase + ((g >> 1) & 1) * 1024 + w4 * 256 + (t >> 1) * 8;
    const uint32_t sel = (g & 1) ? ((t & 1) ? 0x3244u : 0x1044u) : ((t & 1) ? 0x4432u : 0x4410u);
#pragma unroll
    for (int i = 0; i < 16; i++) {
        const uint2 xw = lds64(xp + i * 16);
        bf[i] = make_uint2(prmt(xw.x, 0, sel), prmt(xw.y, 0, sel));
    }
}
__device__ __forceinline__ void gemv_tall(uint32_t wbase, const uint2 (&bf)[16], float* red, int w4, int g, int t) {
    const uint32_t wu = wbase + (128 * w4 + (t & 1) + 4 * (t >> 1)) * 64 + (((g >> 1) ^ (t & 2)) << 4) + (g & 1) * 8;
    const uint32_t wv = (wu + 128) ^ 16;
    float a[4][4];
#pragma unroll
    for (int i = 0; i < 16; i++) (&a[0][0])[i] = 0.f;
#pragma unroll
    for (int i = 0; i < 16; i++) {
        const uint2 u = lds64(wu + i * 512), v = lds64(wv + i * 512);
        mma16816(a[i & 3], u.x, u.y, v.x, v.y, bf[i].x, bf[i].y);
    }
    if (t < 2)
        *(float4*)(red + (w4 * 2 + t) * 32 + 4 * g) =
            make_float4((a[0][0] + a[1][0]) + (a[2][0] + a[3][0]), (a[0][1] + a[1][1]) + (a[2][1] + a[3][1]),
                        (a[0][2] + a[1][2]) + (a[2][2] + a[3][2]), (a[0][3] + a[1][3]) + (a[2][3] + a[3][3]));
}
__device__ __forceinline__ void tall_finish(const float* red, float* dst, int tid, uint32_t tag, int lo = 0, int hi = 64) {
    named_bar(1, 128);
    if (tid >= lo && tid < hi) {
        st_relaxed32(dst, tagw((red[tid] + red[64 + tid]) + (red[128 + tid] + red[192 + tid]), tag));
    }
}

__device__ __forceinline__ void combineA(Scratch& G, int bh, int dq, uint32_t tag, float* red, int tid, const unsigned char* prog) {
    const int r = tid >> 3, c4 = tid & 7, w4 = tid >> 5, lane = tid & 31;
    const float2* ml = G.partML + (bh * 128 + r) * 4;
    const float* po = G.partO + (size_t)(bh * 128 + r) * 128 + dq * 32 + c4 * 4;
    uint2 m[8];
    uint4 o[8];
    uint32_t bad[8];
    STAMP(tid == 0 && bh >= 32, 28);
#pragma unroll
    for (int k = 0; k < 8; k++) m[k] = ld_relaxed64(ml + 64 * k);
#pragma unroll
    for (int k = 0; k < 8; k++) {
        o[k] = make_uint4(~tag, ~tag, ~tag, ~tag);
        ld_relaxed128_if(o[k], po + (size_t)k * 16 * 128, bh < 60);
    }
    unsigned it = 0;
    while (true) {
        uint32_t any = 0;
#pragma unroll
        for (int k = 0; k < 8; k++) { bad[k] = bad2(m[k].x, m[k].y, tag) & 1u; any |= bad[k]; }
        if (!__any_sync(~0u, any)) break;
#pragma unroll
        for (int k = 0; k < 8; k++) ld_relaxed64_if(m[k], ml + 64 * k, bad[k]);
        if (++it > SPIN_LIMIT) __trap();
    }
    STAMP(tid == 0 && bh >= 32, 30);
    STAMP(tid == 0 && bh >= 32, 19);
    float M = fmaxf(fmaxf(fmaxf(__uint_as_float(m[0].x), __uint_as_float(m[1].x)), fmaxf(__uint_as_float(m[2].x), __uint_as_float(m[3].x))),
                    fmaxf(fmaxf(__uint_as_float(m[4].x), __uint_as_float(m[5].x)), fmaxf(__uint_as_float(m[6].x), __uint_as_float(m[7].x))));
    M = fmaxf(M, __shfl_xor_sync(~0u, M, 8));
    M = fmaxf(M, __shfl_xor_sync(~0u, M, 16));
    float wgt[8], L = 0.f;
#pragma unroll
    for (int k = 0; k < 8; k++) {
        wgt[k] = ex2(__uint_as_float(m[k].x) - M);
        L = fmaf(wgt[k], __uint_as_float(m[k].y), L);
    }
    L += __shfl_xor_sync(~0u, L, 8);
    L += __shfl_xor_sync(~0u, L, 16);
    if (lane == 0) { red[128 + w4] = M; red[132 + w4] = L; }
    named_bar(1, 128);
    {
        const float4 Mw = *(float4*)(red + 128), Lw = *(float4*)(red + 132);
        const float Mx = fmaxf(fmaxf(Mw.x, Mw.y), fmaxf(Mw.z, Mw.w));
        const float Lt = (ex2(Mw.x - Mx) * Lw.x + ex2(Mw.y - Mx) * Lw.y) + (ex2(Mw.z - Mx) * Lw.z + ex2(Mw.w - Mx) * Lw.w);
        const float f = ex2(M - Mx) / Lt;
#pragma unroll
        for (int k = 0; k < 8; k++) wgt[k] *= f;
    }
    STAMP(tid == 0 && bh >= 32, 23);
    if (bh >= 60) wait_ticket(prog, NT + YO + (bh - 63) * YOS);
    while (true) {
        uint32_t any = 0;
#pragma unroll
        for (int k = 0; k < 8; k++) { bad[k] = bad4(o[k], tag) & 1u; any |= bad[k]; }
        if (!__any_sync(~0u, any)) break;
#pragma unroll
        for (int k = 0; k < 8; k++) ld_relaxed128_if(o[k], po + (size_t)k * 16 * 128, bad[k]);
        if (++it > SPIN_LIMIT) __trap();
    }
    STAMP(tid == 0 && bh >= 32, 31);
    float a0 = 0.f, a1 = 0.f, a2 = 0.f, a3 = 0.f, b0 = 0.f, b1 = 0.f, b2 = 0.f, b3 = 0.f;
#pragma unroll
    for (int k = 0; k < 8; k += 2) {
        a0 = fmaf(wgt[k], __uint_as_float(o[k].x), a0); b0 = fmaf(wgt[k + 1], __uint_as_float(o[k + 1].x), b0);
        a1 = fmaf(wgt[k], __uint_as_float(o[k].y), a1); b1 = fmaf(wgt[k + 1], __uint_as_float(o[k + 1].y), b1);
        a2 = fmaf(wgt[k], __uint_as_float(o[k].z), a2); b2 = fmaf(wgt[k + 1], __uint_as_float(o[k + 1].z), b2);
        a3 = fmaf(wgt[k], __uint_as_float(o[k].w), a3); b3 = fmaf(wgt[k + 1], __uint_as_float(o[k + 1].w), b3);
    }
    a0 += b0; a1 += b1; a2 += b2; a3 += b3;
#pragma unroll
    for (int s = 8; s <= 16; s <<= 1) {
        a0 += __shfl_xor_sync(~0u, a0, s);
        a1 += __shfl_xor_sync(~0u, a1, s);
        a2 += __shfl_xor_sync(~0u, a2, s);
        a3 += __shfl_xor_sync(~0u, a3, s);
    }
    if (lane < 8) *(float4*)(red + w4 * 32 + c4 * 4) = make_float4(a0, a1, a2, a3);
    named_bar(1, 128);
    STAMP(tid == 0 && bh >= 32, 24);
}

struct Ptrs {
    const __nv_bfloat16 *K, *xA, *xB;
    __nv_bfloat16* out;
    Scratch* g;
};
struct Maps { CUtensorMap m_wq, m_v, m_ckv, m_wqB, m_wuk, m_uv[2], m_w[2]; };

__global__ void __launch_bounds__(NTHREADS, 1)
fused_decode_kernel(const Ptrs P, const __grid_constant__ Maps M) {
    extern __shared__ __align__(1024) unsigned char smem[];
    const uint32_t sb = (uint32_t)__cvta_generic_to_shared(smem);
    uint64_t pol;
    asm("createpolicy.fractional.L2::evict_first.b64 %0, 1.0;" : "=l"(pol));
    asm volatile("{\n.reg .pred p;\nsetp.lt.u32 p, %3, 32;\n@p cp.async.bulk.prefetch.L2.global.L2::cache_hint [%0], %1, %2;\n}\n"
                 ::"l"((const char*)P.K + (blockIdx.x << 14)), "n"(PFB), "l"(pol), "r"(threadIdx.x) : "memory");
    if (threadIdx.x < 32 && elect_one()) {
        mbar_init(sb + SM_BAR + BAR_FULL, 1);
        mbar_init(sb + SM_BAR + BAR_W, 1);
        asm volatile("fence.mbarrier_init.release.cluster;" ::: "memory");
        if (blockIdx.x < NA_CTA) {
            mbar_expect_tx(sb + SM_BAR + BAR_FULL, 16384);
            bulk_load(sb + SM_SLOT, (const char*)P.K + (blockIdx.x << 14), 16384, sb + SM_BAR + BAR_FULL, pol);
        }
        if (blockIdx.x < 128) {
            mbar_expect_tx(sb + SM_BAR + BAR_W, 32768 + 4096);
            issue_tall(sb + SM_WQ, &M.m_wq, slice_of(blockIdx.x) * 32, 0, sb + SM_BAR + BAR_W, pol);
            bulk_load_nohint(sb + SM_P, P.xA, 2048, sb + SM_BAR + BAR_W);
            bulk_load_nohint(sb + SM_P + 2048, P.xB, 2048, sb + SM_BAR + BAR_W);
        }
    }
    const int tid = threadIdx.x, warp = __shfl_sync(~0u, tid >> 5, 0), lane = tid & 31;
    const int g = lane >> 2, t = lane & 3;
    const int cta = blockIdx.x;
    Scratch& G = *P.g;
    const bool isB = cta >= NA_CTA;
    const bool hasSlice = cta < 128;
    const int j = slice_of(cta), h = j >> 2, qd = cta & 3;
    const int mat = j >> 6, cg = j & 7, rg = (j >> 3) & 7;
    const bool late = j < JE0 || j >= 124;
    STAMP(tid == 32, 0);
    if (warp == 7) {
        __syncthreads();
        const uint32_t epoch = *(volatile uint32_t*)(smem + SM_BAR + W_EPOCH);
        const uint32_t tag = (epoch + 1) & 1;
        if (!isB) { mbar_wait(sb + SM_BAR + BAR_W, 0); __nanosleep(QDELAY); }
#pragma unroll 1
        for (int i = 0; i < 8; i++) {
            if (i == 4 && !isB) wait_prog(smem + SM_BAR + W_PROG, 16 * 128);
            if (i == 0 && isB) { mbar_wait(sb + SM_BAR + BAR_QABS, 0); __nanosleep(8000); }
            uint4 v[8];
            uint32_t bad[8];
#pragma unroll
            for (int k = 0; k < 8; k++) { bad[k] = 1; v[k] = make_uint4(0, 0, 0, 0); }
            unsigned it = 0;
            while (true) {
#pragma unroll
                for (int k = 0; k < 8; k++) ld_relaxed128_if(v[k], G.qA + (8 * i + k) * 128 + lane * 4, bad[k]);
                uint32_t any = 0;
#pragma unroll
                for (int k = 0; k < 8; k++) { bad[k] = bad4(v[k], tag) & 1u; any |= bad[k]; }
                if (!__any_sync(~0u, any)) break;
                __nanosleep(40);
                if (++it > SPIN_LIMIT) __trap();
            }
#pragma unroll
            for (int k = 0; k < 8; k++) {
                uint32_t* dst = (uint32_t*)(smem + SM_QA + (8 * i + k) * 256 + (lane >> 1) * 16 + (lane & 1) * 4);
                dst[0] = pack_bf16(__uint_as_float(v[k].x), __uint_as_float(v[k].y));
                dst[2] = pack_bf16(__uint_as_float(v[k].z), __uint_as_float(v[k].w));
            }
            __syncwarp();
            if (lane == 0) mbar_arrive(sb + SM_BAR + BAR_Q + i * 8);
            STAMP(lane == 0 && i == 0, 2);
        }
        STAMP(lane == 0, 21);
        if (hasSlice && lane == 0) {
            mbar_wait(sb + SM_BAR + BAR_PDONE, 0);
#pragma unroll 1
            for (int p = 0; p < 512 / PV + 512 / PR; p++) {
                const bool uv = p < 512 / PV;
                const int r = uv ? p * PV : (p - 512 / PV) * PR;
                if (!uv || late)
                    wait_ticket(smem + SM_BAR + W_PROG, NT + (uv ? YV + (r * DV >> 8) : YW + (r * DW >> 7) + (r + PR == 512 ? DL : 0)));
                STAMP(p == 0, 10);
                const bool tail = !uv && r >= 384 + 32 * RA;
                const uint32_t bar = sb + SM_BAR + BAR_S + (uv ? r >> 8 : (tail ? 6 : 2 + (r >> 7))) * 8;
                if (uv ? (r & 255) == 0 : ((r & 127) == 0 || r == 384 + 32 * RA))
                    mbar_expect_tx(bar, uv || r < 384 ? 16384 : (tail ? (4 - RA) * 4096 : RA * 4096));
                tma_2d(sb + SM_SQ + (uv ? r * 64 : 32768 + r * 128), uv ? &M.m_uv[late] : &M.m_w[mat], uv ? j * 32 : cg * 64,
                       uv ? r : (rg + 8 * (r >> 7)) * 128 + (r & 127), bar, pol);
            }
        }
    } else if (warp >= 4) {
        const int wi = warp - 4;
        const uint32_t slot = sb + SM_SLOT + wi * 32768;
        const uint32_t bar = sb + SM_BAR + BAR_FULL + wi * 16, barV = bar + 8;
        unsigned tk = wi * NA_CTA + cta;
        const int ev = wi;
        if (lane == 0) {
            if (wi) mbar_init(bar, 1);
            mbar_init(barV, 1);
            if (isB && wi == 0) {
                for (int s = 0; s < 5; s++) {
                    mbar_init(sb + SM_BAR + BAR_BFULL + s * 8, 1);
                    mbar_init(sb + SM_BAR + BAR_BEMPTY + s * 8, 4);
                }
            }
            asm volatile("fence.mbarrier_init.release.cluster;" ::: "memory");
        }
        __syncthreads();
        const uint32_t epoch = *(volatile uint32_t*)(smem + SM_BAR + W_EPOCH);
        const uint32_t tag = (epoch + 1) & 1;

        bool active = true;
        if (isB) {
            if (wi == 1 && lane == 0) {
                wait_counter(&G.cntQabs.v, (epoch + 1) * 128, 64);
                fence_proxy_async();
                mbar_expect_tx(sb + SM_BAR + BAR_QABS, 32768);
                bulk_load_nohint(sb + SM_SLOT + 5 * 32768, G.qabs + ((cta - NA_CTA) >> 3) * 16384, 32768, sb + SM_BAR + BAR_QABS);
            }
            if (wi == 0 && lane == 0) {
                const int ib = cta - NA_CTA;
                int s = 0, sl = 0; uint32_t ph = 1, phl = 0;
                for (int u = 0; u < 32; u++) {
                    if (u >= BINFL) {
                        mbar_wait(sb + SM_BAR + BAR_BFULL + sl * 8, phl);
                        LAND(true, 16384 + ib * 32 + u);
                        if (++sl == 5) { sl = 0; phl ^= 1; }
                    }
                    if (u == 3 && hasSlice) mbar_wait(sb + SM_BAR + BAR_WFREE, 0);
                    mbar_wait(sb + SM_BAR + BAR_BEMPTY + s * 8, ph);
                    const uint32_t fb = sb + SM_BAR + BAR_BFULL + s * 8;
                    const int row = (ib >> 3) * 8192 + ((u >> 1) * 8 + (ib & 7)) * 64;
                    mbar_expect_tx(fb, 32768);
                    for (int x = 0; x < 4; x++)
                        tma_2d(sb + SM_SLOT + s * 32768 + x * 8192, &M.m_ckv, ((u & 1) * 4 + x) * 64, row, fb, pol);
                    if (++s == 5) { s = 0; ph ^= 1; }
                }
            }
            __syncwarp();
            mbar_wait(sb + SM_BAR + BAR_BDONE, 0);
            if (lane == 0) tk = NSTATIC + atomicInc(&G.ticket.v, DRAWS - 1);
            tk = __shfl_sync(~0u, tk, 0);
            active = tk < NT;
        } else if (ev != 0) {
            __syncwarp();
            mbar_wait(sb + SM_BAR + BAR_W + (ev - 1) * 8, 0);
        }
        if (active) {
            if ((isB || ev != 0) && lane == 0) {
                mbar_expect_tx(bar, 16384);
                bulk_load(slot, (const char*)P.K + (size_t)tk * 16384, 16384, bar, pol);
            }
            const uint32_t kA = slot + g * 256 + t * 16 + (g & 1) * 64, kB = kA ^ 64;
            const uint32_t qo = t * 16 + ((g >> 1) & 1) * 64 + (g & 1) * 8;
            const uint32_t v0 = slot + 16384 + (2 * t) * 128 + ((g ^ (2 * t)) << 4), v1 = (v0 + 128) ^ 16;
            const uint32_t sl0 = (g & 1) ? 0x1044u : 0x4410u, sl1 = (g & 1) ? 0x3244u : 0x4432u;
            const uint32_t sa0 = (g & 2) ? 0x4444u : sl0, sa1 = (g & 2) ? 0x4444u : sl1;
            const uint32_t sb0 = (g & 2) ? sl0 : 0x4444u, sb1 = (g & 2) ? sl1 : 0x4444u;
            const int d0 = 64 * (t >> 1) + 8 * g + 4 * (t & 1);
            uint32_t ph = 0;
            while (true) {
                const uint32_t qa = sb + SM_QA + (tk >> 7) * 256 + qo;
                bool vout = false;
                if (XRV && lane == 0 && tk >= NT - XRV && !mbar_wait_for(bar, ph, TV)) {
                    mbar_expect_tx(barV, 16384);
                    tma_3d(slot + 16384, &M.m_v, tk * 64, 0, barV, pol);
                    vout = true;
                }
                if (XRV) __syncwarp();
                mbar_wait(bar, ph);
                LAND(lane == 0, tk);
                unsigned nxt = 0;
                if (lane == 0) {
                    if (!vout) {
                        mbar_expect_tx(barV, 16384);
                        tma_3d(slot + 16384, &M.m_v, tk * 64, 0, barV, pol);
                    }
                    asm volatile("atom.relaxed.gpu.global.inc.u32 %0, [%1], %2;" : "=r"(nxt) : "l"(&G.ticket.v), "r"(DRAWS - 1) : "memory");
                }
                __syncwarp();
                mbar_wait(sb + SM_BAR + BAR_Q + (tk >> 10) * 8, 0);
                STAMP(tid == 128 && tk < NSTATIC, 3);
                uint2 qf[4];
                qf[0] = lds64(qa); qf[1] = lds64(qa ^ 64); qf[2] = lds64(qa + 128); qf[3] = lds64((qa ^ 64) + 128);
                float c[8][4];
#pragma unroll
                for (int i = 0; i < 32; i++) (&c[0][0])[i] = 0.f;
#pragma unroll
                for (int s = 0; s < 4; s++)
#pragma unroll
                    for (int jj = 0; jj < 8; jj++) {
                        const uint4 u = lds128(((s & 1) ? kB : kA) + jj * 2048 + (s >> 1) * 128);
                        mma16816(c[jj], u.x, u.y, u.z, u.w, qf[s].x, qf[s].y);
                    }
                float sc[8];
#pragma unroll
                for (int jj = 0; jj < 8; jj++) sc[jj] = c[jj][0] + c[jj][3];
#pragma unroll
                for (int jj = 0; jj < 8; jj += 2) scale_scores(sc[jj], sc[jj + 1]);
                float m = fmaxf(fmaxf(fmaxf(sc[0], sc[1]), fmaxf(sc[2], sc[3])), fmaxf(fmaxf(sc[4], sc[5]), fmaxf(sc[6], sc[7])));
                m = fmaxf(m, __shfl_xor_sync(~0u, m, 5));
                m = fmaxf(m, __shfl_xor_sync(~0u, m, 8));
                m = fmaxf(m, __shfl_xor_sync(~0u, m, 16));
                const float ms = __uint_as_float(tagw(m * LOG2E, tag));
                uint32_t W0[4], W1[4];
                float l = 0.f;
#pragma unroll
                for (int i = 0; i < 4; i++) {
                    const uint32_t pp = pack_bf16(ex2(fmaf(sc[2 * i], LOG2E, -ms)), ex2(fmaf(sc[2 * i + 1], LOG2E, -ms)));
                    W0[i] = __shfl_sync(~0u, pp, 8 * t);
                    W1[i] = __shfl_sync(~0u, pp, 8 * t + 5);
                    l += bf_lo(pp) + bf_hi(pp);
                }
                l += __shfl_xor_sync(~0u, l, 5);
                l += __shfl_xor_sync(~0u, l, 8);
                l += __shfl_xor_sync(~0u, l, 16);
                if (lane == 0 || lane == 2)
                    st_relaxed128((char*)G.partML + tk * 32 + lane * 8, __float_as_uint(ms), tagw(l, tag), __float_as_uint(ms), tagw(l, tag));
                uint32_t pb[16][2];
#pragma unroll
                for (int i = 0; i < 16; i++) {
                    const uint32_t pw = (i & 1) ? W1[i >> 2] : W0[i >> 2];
                    pb[i][0] = prmt(pw, 0, (i & 2) ? sa1 : sa0);
                    pb[i][1] = prmt(pw, 0, (i & 2) ? sb1 : sb0);
                    asm volatile("" : "+r"(pb[i][0]), "+r"(pb[i][1]));
                }
                float* po = G.partO + (size_t)tk * 128 + d0;
                asm volatile("" : "+l"(po));
                if (lane == 0) note_draw(smem + SM_BAR + W_PROG, nxt);
                nxt += NSTATIC;
                if (nxt >= NT - XPK && nxt < NT && lane == 0) {
                    mbar_expect_tx(bar, 16384);
                    bulk_load(slot, (const char*)P.K + (size_t)nxt * 16384, 16384, bar, pol);
                }
                mbar_wait(barV, ph);
                LAND(lane == 0, 8192 + tk);
                ph ^= 1;
                if (nxt < NT - XPK && lane == 0) {
                    mbar_expect_tx(bar, 16384);
                    bulk_load(slot, (const char*)P.K + (size_t)nxt * 16384, 16384, bar, pol);
                }
                __syncwarp();
                float acc[2][4][4];
#pragma unroll
                for (int i = 0; i < 32; i++) (&acc[0][0][0])[i] = 0.f;
#pragma unroll
                for (int jj = 0; jj < 8; jj++)
#pragma unroll
                    for (int e = 0; e < 2; e++)
#pragma unroll
                        for (int hh = 0; hh < 2; hh++) {
                            const uint4 u = lds128((e ? v1 : v0) + jj * 1024 + hh * 8192);
                            mma16816(acc[hh][(jj & 1) * 2 + e], u.x, u.y, u.z, u.w, pb[2 * jj + e][0], pb[2 * jj + e][1]);
                        }
                float r4[4];
#pragma unroll
                for (int i = 0; i < 4; i++) {
                    const float x0 = (acc[0][0][i] + acc[0][1][i]) + (acc[0][2][i] + acc[0][3][i]);
                    const float x1 = (acc[1][0][i] + acc[1][1][i]) + (acc[1][2][i] + acc[1][3][i]);
                    r4[i] = (t & 2) ? x1 : x0;
                }
                st_relaxed128(po, tagw(r4[0], tag), tagw(r4[1], tag), tagw(r4[2], tag), tagw(r4[3], tag));
                nxt = __shfl_sync(~0u, nxt, 0);
                if (nxt >= NT) break;
                tk = nxt;
            }
            STAMP(lane == 0, 16 + wi);
        } else if (lane == 0) {
            note_draw(smem + SM_BAR + W_PROG, tk - NSTATIC);
        }
    } else {
        float* red = (float*)(smem + SM_RED2);
        if (tid == 32) {
            const uint32_t ep0 = ld_relaxed32(&G.epoch.v);
            for (int e = 0; e < 8; e++) mbar_init(sb + SM_BAR + BAR_Q + e * 8, 1);
            for (int e = 1; e < 10; e++) mbar_init(sb + SM_BAR + BAR_W + e * 8, 1);
            mbar_init(sb + SM_BAR + BAR_BDONE, 1);
            mbar_init(sb + SM_BAR + BAR_PDONE, 1);
            mbar_init(sb + SM_BAR + BAR_QABS, 1);
            mbar_init(sb + SM_BAR + BAR_WFREE, 1);
            asm volatile("fence.mbarrier_init.release.cluster;" ::: "memory");
            asm volatile("st.volatile.shared.v4.u32 [%0], {%1, %2, %1, %1};" ::"r"(sb + SM_BAR + W_PROG), "r"(0), "r"(now_ns()) : "memory");
            *(volatile uint32_t*)(smem + SM_BAR + W_EPOCH) = ep0;
        } else if (tid == 64) {
            asm volatile("prefetch.tensormap [%0];" ::"l"(&M.m_v) : "memory");
            asm volatile("prefetch.tensormap [%0];" ::"l"(&M.m_wqB) : "memory");
            asm volatile("prefetch.tensormap [%0];" ::"l"(&M.m_wuk) : "memory");
        }
        __syncthreads();
        const uint32_t epoch = *(volatile uint32_t*)(smem + SM_BAR + W_EPOCH);
        const uint32_t tag = (epoch + 1) & 1;
        STAMP(tid == 0, 14);

        if (hasSlice) {
            const uint32_t nt = tag ^ 1;
            const int qoff = ((tid >> 5) & 1) * 4096 + 32 * j + (tid & 31);
            if (tid < 64) {
                st_relaxed32(G.qA + qoff, nt); st_relaxed32(G.qB + qoff, nt);
                if (tid < 32) {
                    st_relaxed32(G.o + 32 * j + tid, nt); st_relaxed32(G.o + 4096 + 32 * j + tid, nt);
                    st_relaxed32(G.ctx + 32 * j + tid, nt); st_relaxed32(G.ctx + 4096 + 32 * j + tid, nt);
                }
            }
            if (tid >= 64 && tid < 72) st_relaxed32((uint32_t*)P.out + 8 * j + (tid - 64), 0);
            mbar_wait(sb + SM_BAR + BAR_W, 0);
            LAND(tid == 0, 17408 + 0 * 128 + j);
            if (tid == 96) {
                mbar_expect_tx(sb + SM_BAR + BAR_W + 8, 32768);
                issue_tall(sb + SM_WQB, &M.m_wqB, j * 32, 0, sb + SM_BAR + BAR_W + 8, pol);
            }
            __syncwarp();
            STAMP(tid == 0, 15);
            uint2 bf[16];
            tall_prep(bf, sb + SM_P, warp, g, t);
            gemv_tall(sb + SM_WQ, bf, (float*)(smem + SM_RED1), warp, g, t);
            tall_finish((float*)(smem + SM_RED1), G.qA + qoff, tid, tag, 0, h >= HCLR ? 32 : 64);
            STAMP(tid == 0, 1);
            tall_prep(bf, sb + SM_P + 2048, warp, g, t);
            mbar_wait(sb + SM_BAR + BAR_W + 8, 0);
            LAND(tid == 0, 17408 + 1 * 128 + j);
            if (tid == 96) {
                mbar_expect_tx(sb + SM_BAR + BAR_W + 16, 32768);
                tma_2d(sb + SM_WUK, &M.m_wuk, h * 128, qd * 128, sb + SM_BAR + BAR_W + 16, pol);
            }
            __syncwarp();
            gemv_tall(sb + SM_WQB, bf, red, warp, g, t);
            tall_finish(red, G.qB + qoff, tid, tag);
            if (tid == 96) mbar_arrive(sb + SM_BAR + BAR_WFREE);
            STAMP(tid == 0, 25);
            named_bar(1, 128);
            uint4 qf[4];
            {
                const float* qp = G.qB + ((g & 1) * 32 + h) * 128 + t * 8;
                uint4 v[8];
                unsigned it = 0;
                while (true) {
                    uint32_t bad = 0;
#pragma unroll
                    for (int i = 0; i < 8; i++) v[i] = ld_relaxed128(qp + (i >> 1) * 32 + (i & 1) * 4);
#pragma unroll
                    for (int i = 0; i < 8; i++) bad |= bad4(v[i], tag);
                    if (!__any_sync(~0u, bad & 1u)) break;
                    __nanosleep(100);
                    if (++it > SPIN_LIMIT) __trap();
                }
#pragma unroll
                for (int s = 0; s < 4; s++)
                    qf[s] = make_uint4(pack_bf16(__uint_as_float(v[2 * s].x), __uint_as_float(v[2 * s].y)),
                                       pack_bf16(__uint_as_float(v[2 * s].z), __uint_as_float(v[2 * s].w)),
                                       pack_bf16(__uint_as_float(v[2 * s + 1].x), __uint_as_float(v[2 * s + 1].y)),
                                       pack_bf16(__uint_as_float(v[2 * s + 1].z), __uint_as_float(v[2 * s + 1].w)));
            }
            mbar_wait(sb + SM_BAR + BAR_W + 16, 0);
            LAND(tid == 0, 17408 + 2 * 128 + j);
#pragma unroll
            for (int jj = 0; jj < 2; jj++) {
                float c[4] = {0.f, 0.f, 0.f, 0.f};
#pragma unroll
                for (int s = 0; s < 4; s++) {
                    const uint32_t a = sb + SM_WUK + (32 * warp + 16 * jj + g) * 256 + (t + 4 * s) * 16;
                    const uint4 u = lds128(a), v = lds128(a + 2048);
                    mma16816(c, u.x, v.x, u.y, v.y, qf[s].x, qf[s].y);
                    mma16816(c, u.z, v.z, u.w, v.w, qf[s].z, qf[s].w);
                }
                const float val = (t & 2) ? ((t & 1) ? c[3] : c[2]) : ((t & 1) ? c[1] : c[0]);
                const int cc = 128 * qd + 32 * warp + 16 * jj + g + ((t & 2) ? 8 : 0);
                const int off = (cc >> 6) * 2048 + h * 64 + ((((cc & 63) >> 3) ^ (h & 7)) << 3) + (cc & 7);
                G.qabs[(t & 1) * 16384 + off] = __float2bfloat16(val);
            }
            named_bar(1, 128);
            if (tid == 0) red_release(&G.cntQabs.v);
            STAMP(tid == 0, 4);
            if (h >= HCLR) {
#pragma unroll
                for (int k = 0; k < 8; k++)
                    st_relaxed128(G.partO + (size_t)((32 + h) * 128 + 16 * k + (tid >> 3)) * 128 + qd * 32 + (tid & 7) * 4, nt, nt, nt, nt);
                if (tid < 64) st_relaxed128((char*)G.partML + ((32 + h) * 128 + qd * 32) * 32 + tid * 16, nt, nt, nt, nt);
                __threadfence();
                tall_finish((float*)(smem + SM_RED1), G.qA + qoff, tid, tag, 32, 64);
            }
        }

        if (isB) {
            const int ib = cta - NA_CTA;
            float acc[8][16];
#pragma unroll
            for (int i = 0; i < 8; i++)
#pragma unroll
                for (int k = 0; k < 16; k++) acc[i][k] = 0.f;
            float mrun[8], lrun[8];
#pragma unroll
            for (int i = 0; i < 8; i++) { mrun[i] = -INFINITY; lrun[i] = 0.f; }
            const uint64_t dQ = make_desc(sb + SM_SLOT + 5 * 32768);
            const uint64_t dP = make_desc(sb + SM_P);
            const uint32_t pst = sb + SM_P + (((lane >> 4) * 8 + (lane & 7)) * 128) + (((2 * warp + ((lane >> 3) & 1)) ^ (lane & 7)) << 4);
            mbar_wait(sb + SM_BAR + BAR_QABS, 0);
            STAMP(tid == 0, 5);
            int s0 = 0; uint32_t ph0 = 0;
            for (int it = 0; it < 16; it++) {
                int s1 = s0 + 1; uint32_t ph1 = ph0;
                if (s1 == 5) { s1 = 0; ph1 ^= 1; }
                const uint64_t dA0 = make_desc(sb + SM_SLOT + s0 * 32768), dA1 = make_desc(sb + SM_SLOT + s1 * 32768);
                float S[16];
                mbar_wait(sb + SM_BAR + BAR_BFULL + s0 * 8, ph0);
                mbar_wait(sb + SM_BAR + BAR_BFULL + s1 * 8, ph1);
                wg_fence();
#pragma unroll
                for (int k = 0; k < 32; k++) {
                    const uint64_t da = ((k < 16) ? dA0 : dA1) + (uint64_t)((((k >> 2) & 3) * 8192 + (k & 3) * 32) >> 4);
                    const uint64_t db = dQ + (uint64_t)(((k >> 2) * 4096 + (k & 3) * 32) >> 4);
                    wgmma_n32<0>(S, da, db, k > 0);
                }
                wg_commit();
                wg_wait<0>();
#pragma unroll
                for (int i = 0; i < 16; i++) S[i] *= SCALE;
                float mx[8];
#pragma unroll
                for (int i = 0; i < 8; i++) {
                    mx[i] = fmaxf(S[4 * (i >> 1) + (i & 1)], S[4 * (i >> 1) + 2 + (i & 1)]);
                    mx[i] = fmaxf(mx[i], __shfl_xor_sync(~0u, mx[i], 4));
                    mx[i] = fmaxf(mx[i], __shfl_xor_sync(~0u, mx[i], 8));
                    mx[i] = fmaxf(mx[i], __shfl_xor_sync(~0u, mx[i], 16));
                }
                if (g == 0) {
#pragma unroll
                    for (int jb = 0; jb < 4; jb++)
                        *(float2*)(red + warp * 32 + 8 * jb + 2 * t) = make_float2(mx[2 * jb], mx[2 * jb + 1]);
                }
                named_bar(1, 128);
                float al[8];
                bool chg = false;
                uint32_t R[8];
#pragma unroll
                for (int jb = 0; jb < 4; jb++) {
                    float2 a = *(float2*)(red + 8 * jb + 2 * t), b = *(float2*)(red + 32 + 8 * jb + 2 * t);
                    float2 c = *(float2*)(red + 64 + 8 * jb + 2 * t), d = *(float2*)(red + 96 + 8 * jb + 2 * t);
                    const float n0 = fmaxf(mrun[2 * jb], fmaxf(fmaxf(a.x, b.x), fmaxf(c.x, d.x)) * LOG2E);
                    const float n1 = fmaxf(mrun[2 * jb + 1], fmaxf(fmaxf(a.y, b.y), fmaxf(c.y, d.y)) * LOG2E);
                    chg |= (n0 != mrun[2 * jb]) | (n1 != mrun[2 * jb + 1]);
                    al[2 * jb] = ex2(mrun[2 * jb] - n0);
                    al[2 * jb + 1] = ex2(mrun[2 * jb + 1] - n1);
                    mrun[2 * jb] = n0; mrun[2 * jb + 1] = n1;
                    R[2 * jb]     = pack_bf16(ex2(fmaf(S[4 * jb], LOG2E, -n0)), ex2(fmaf(S[4 * jb + 1], LOG2E, -n1)));
                    R[2 * jb + 1] = pack_bf16(ex2(fmaf(S[4 * jb + 2], LOG2E, -n0)), ex2(fmaf(S[4 * jb + 3], LOG2E, -n1)));
                    lrun[2 * jb]     = fmaf(lrun[2 * jb], al[2 * jb], bf_lo(R[2 * jb]) + bf_lo(R[2 * jb + 1]));
                    lrun[2 * jb + 1] = fmaf(lrun[2 * jb + 1], al[2 * jb + 1], bf_hi(R[2 * jb]) + bf_hi(R[2 * jb + 1]));
                }
                asm volatile("stmatrix.sync.aligned.m8n8.x4.trans.shared.b16 [%0], {%1,%2,%3,%4};"
                             ::"r"(pst), "r"(R[0]), "r"(R[1]), "r"(R[2]), "r"(R[3]) : "memory");
                asm volatile("stmatrix.sync.aligned.m8n8.x4.trans.shared.b16 [%0], {%1,%2,%3,%4};"
                             ::"r"(pst + 2048), "r"(R[4]), "r"(R[5]), "r"(R[6]), "r"(R[7]) : "memory");
                asm volatile("fence.proxy.async.shared::cta;" ::: "memory");
                if (__any_sync(~0u, chg)) {
#pragma unroll
                    for (int mt = 0; mt < 8; mt++)
#pragma unroll
                        for (int k = 0; k < 16; k++) acc[mt][k] *= al[2 * (k >> 2) + (k & 1)];
                }
                named_bar(1, 128);
                wg_fence();
#pragma unroll
                for (int mt = 0; mt < 4; mt++)
#pragma unroll
                    for (int kk = 0; kk < 4; kk++)
                        wgmma_n32<1>(acc[mt], dA0 + (uint64_t)((mt * 8192 + kk * 2048) >> 4), dP + (uint64_t)((kk * 32) >> 4), 1);
                wg_commit();
#pragma unroll
                for (int mt = 0; mt < 4; mt++)
#pragma unroll
                    for (int kk = 0; kk < 4; kk++)
                        wgmma_n32<1>(acc[4 + mt], dA1 + (uint64_t)((mt * 8192 + kk * 2048) >> 4), dP + (uint64_t)((kk * 32) >> 4), 1);
                wg_commit();
                wg_wait<1>();
                if (lane == 0) mbar_arrive(sb + SM_BAR + BAR_BEMPTY + s0 * 8);
                wg_wait<0>();
                if (lane == 0) mbar_arrive(sb + SM_BAR + BAR_BEMPTY + s1 * 8);
                s0 = s1 + 1; ph0 = ph1;
                if (s0 == 5) { s0 = 0; ph0 ^= 1; }
            }
#pragma unroll
            for (int i = 0; i < 8; i++) {
                lrun[i] += __shfl_xor_sync(~0u, lrun[i], 4);
                lrun[i] += __shfl_xor_sync(~0u, lrun[i], 8);
                lrun[i] += __shfl_xor_sync(~0u, lrun[i], 16);
            }
            if (g == 0) {
#pragma unroll
                for (int jb = 0; jb < 4; jb++) {
                    *(float2*)(red + 128 + warp * 32 + 8 * jb + 2 * t) = make_float2(lrun[2 * jb], lrun[2 * jb + 1]);
                    if (warp == 0) *(float2*)(red + 256 + 8 * jb + 2 * t) = make_float2(mrun[2 * jb], mrun[2 * jb + 1]);
                }
            }
            named_bar(1, 128);
            if (tid == 0) mbar_arrive(sb + SM_BAR + BAR_BDONE);
            if (tid < 32)
                G.bml[ib * 32 + tid] = make_float2(red[256 + tid], red[128 + tid] + red[160 + tid] + red[192 + tid] + red[224 + tid]);
            float* bp = G.bpart + (size_t)ib * 16384 + (2 * t) * 512 + 16 * warp + g;
#pragma unroll
            for (int mt = 0; mt < 8; mt++)
#pragma unroll
                for (int k = 0; k < 16; k++)
                    bp[(8 * (k >> 2) + (k & 1)) * 512 + 64 * mt + ((k >> 1) & 1) * 8] = acc[mt][k];
            named_bar(1, 128);
            if (tid == 0) red_release(&G.cntB.v);
            STAMP(tid == 0, 6);
        }

        if (hasSlice) {
            if (tid == 0) {
                wait_prog(smem + SM_BAR + W_PROG, TUV);
                wait_counter(&G.cntB.v, (epoch + 1) * NB_CTA, 500);
                if (cta == 0) st_relaxed32(&G.epoch.v, epoch + 1);
                asm volatile("prefetch.tensormap [%0];" ::"l"(&M.m_uv[late]) : "memory");
                asm volatile("prefetch.tensormap [%0];" ::"l"(&M.m_w[mat]) : "memory");
            }
            named_bar(1, 128);
            if (tid == 32) mbar_arrive(sb + SM_BAR + BAR_PDONE);
            STAMP(tid == 0, 7);
            {
                const int b = tid >> 6, cp = tid & 63;
                uint2 ml[8];
#pragma unroll
                for (int i = 0; i < 8; i++) ml[i] = ld_relaxed64(G.bml + (b * 8 + i) * 32 + h);
                uint4 pv[2][8];
#pragma unroll
                for (int i = 0; i < 16; i++)
                    pv[i >> 3][i & 7] = ld_relaxed128(G.bpart + (size_t)(b * 8 + (i & 7)) * 16384 + h * 512 + (i >> 3) * 256 + 4 * cp);
                float M = __uint_as_float(ml[0].x);
#pragma unroll
                for (int i = 1; i < 8; i++) M = fmaxf(M, __uint_as_float(ml[i].x));
                float L = 0.f, wgt[8];
#pragma unroll
                for (int i = 0; i < 8; i++) {
                    wgt[i] = ex2(__uint_as_float(ml[i].x) - M);
                    L = fmaf(wgt[i], __uint_as_float(ml[i].y), L);
                }
                const float inv = 1.f / L;
#pragma unroll
                for (int x = 0; x < 2; x++) {
                    float v0 = 0.f, v1 = 0.f, v2 = 0.f, v3 = 0.f;
#pragma unroll
                    for (int i = 0; i < 8; i++) {
                        v0 = fmaf(wgt[i], __uint_as_float(pv[x][i].x), v0);
                        v1 = fmaf(wgt[i], __uint_as_float(pv[x][i].y), v1);
                        v2 = fmaf(wgt[i], __uint_as_float(pv[x][i].z), v2);
                        v3 = fmaf(wgt[i], __uint_as_float(pv[x][i].w), v3);
                    }
                    *(uint2*)(smem + SM_P + b * 1024 + x * 512 + cp * 8) = make_uint2(pack_bf16(v0 * inv, v1 * inv), pack_bf16(v2 * inv, v3 * inv));
                }
            }
            STAMP(tid == 0, 8);
        }
        {
            named_bar(1, 128);
#pragma unroll 1
            for (uint64_t plan = j < 64 ? 0xF7351260ull : (j < 124 ? (late ? 0xF75314260ull : 0xF7514603ull) : (hasSlice ? 0xF753426ull : 0xF10ull));
                 plan != 0xF; plan >>= 4) {
                const int step = plan & 15;
                if ((step & 14) == 4) {
                    const int hh = rg + 8 * warp;
                    const uint32_t real = step & 1, both = real & (mat | (warp != 3));
                    if (both) wait_ticket(smem + SM_BAR + W_PROG, mat ? NT + YB : min((33 + hh) * 128 + LAGT, NT + YLATE) + YX);
                    __syncwarp();
                    const float* src = (mat ? G.ctx : G.o) + hh * 128 + lane * 4;
                    uint4 v[2];
                    v[0] = v[1] = make_uint4(tag, tag, tag, tag);
                    uint32_t bad0 = real, bad1 = both;
                    unsigned it = 0;
                    while (true) {
                        ld_relaxed128_if(v[0], src, bad0);
                        ld_relaxed128_if(v[1], src + 4096, bad1);
                        bad0 = bad4(v[0], tag) & 1u; bad1 = bad4(v[1], tag) & 1u;
                        if (!__any_sync(~0u, bad0 | bad1)) break;
                        if (++it > SPIN_LIMIT) __trap();
                    }
#pragma unroll
                    for (int b = 0; b < 2; b++)
                        *(uint2*)(smem + SM_VEC + V_X + b * XSTR + (128 * warp + 4 * lane) * 2) =
                            make_uint2(pack_bf16(__uint_as_float(v[b].x), __uint_as_float(v[b].y)), pack_bf16(__uint_as_float(v[b].z), __uint_as_float(v[b].w)));
                    named_bar(1, 128);
                    STAMP(tid == 0, 29);
                } else if (step >= 6) {
                    const uint32_t real = step & 1;
                    const uint32_t xa = sb + SM_VEC + V_X + ((lane >> 1) & 1) * XSTR + 8 * (lane >> 3) * 2;
                    const uint32_t wa = sb + SM_SQ + 2 * 16384 + (8 * (lane >> 4) + (lane & 7)) * 128 +
                                        (((2 * warp + ((lane >> 3) & 1)) ^ (lane & 7)) << 4);
                    const uint32_t bs = sb + SM_BAR + BAR_S + 16;
                    const float* src = G.o + 4096 + (24 + rg) * 128 + lane * 4;
                    const uint32_t needx = real & (mat ^ 1);
                    uint32_t* dst = (uint32_t*)P.out + (t & 1) * 512 + mat * 256 + cg * 32 + warp * 8 + (t >> 1) * 4 + (g >> 1);
                    asm volatile("" : "+l"(dst));
                    uint4 v = make_uint4(tag, tag, tag, tag);
                    float d[4][4];
#pragma unroll
                    for (int i = 0; i < 16; i++) (&d[0][0])[i] = 0.f;
#pragma unroll 1
                    for (int u = 0; u < 3; u++) {
                        uint4 xf[4];
                        if (needx && u == XU) wait_ticket(smem + SM_BAR + W_PROG, NT + YP + (rg - 7) * YPS);
                        __syncwarp();
                        ld_relaxed128_if(v, src, needx & (u == XU));
#pragma unroll
                        for (int i = 0; i < 4; i++) xf[i] = ldsm4(xa + u * 256 + i * 64);
                        if (real) mbar_wait_nt(bs + u * 8, 0);
#pragma unroll
                        for (int i = 0; i < 4; i++) {
                            const uint4 w0 = ldsm4t(wa + u * 16384 + i * 4096), w1 = ldsm4t(wa + u * 16384 + i * 4096 + 2048);
                            mma16816(d[(i & 1) * 2], w0.x, w0.y, w0.z, w0.w, xf[i].x, xf[i].y);
                            mma16816(d[(i & 1) * 2 + 1], w1.x, w1.y, w1.z, w1.w, xf[i].z, xf[i].w);
                        }
                    }
                    unsigned it = 0;
                    while (__any_sync(~0u, bad4(v, tag) & 1u)) {
                        if (++it > SPIN_LIMIT) __trap();
                        v = ld_relaxed128(src);
                    }
                    STAMP(tid == 96, 20);
                    if (!mat)
                        *(uint2*)(smem + SM_VEC + V_X + XSTR + (384 + 4 * lane) * 2) =
                            make_uint2(pack_bf16(__uint_as_float(v.x), __uint_as_float(v.y)), pack_bf16(__uint_as_float(v.z), __uint_as_float(v.w)));
                    __syncwarp();
                    uint4 xf[4], w[8];
#pragma unroll
                    for (int i = 0; i < 4; i++) xf[i] = ldsm4(xa + 3 * 256 + i * 64);
                    if (real) mbar_wait_nt(bs + 24, 0);
#pragma unroll
                    for (int i = 0; i < 2 * RA; i++) w[i] = ldsm4t(wa + 3 * 16384 + i * 2048);
#pragma unroll
                    for (int i = 0; i < RA; i++) {
                        mma16816(d[(i & 1) * 2], w[2 * i].x, w[2 * i].y, w[2 * i].z, w[2 * i].w, xf[i].x, xf[i].y);
                        mma16816(d[(i & 1) * 2 + 1], w[2 * i + 1].x, w[2 * i + 1].y, w[2 * i + 1].z, w[2 * i + 1].w, xf[i].z, xf[i].w);
                    }
                    if (RA < 4) {
#pragma unroll
                        for (int i = 0; i < 4; i++) {
                            d[0][i] = (d[0][i] + d[1][i]) + (d[2][i] + d[3][i]);
                            d[1][i] = d[2][i] = d[3][i] = 0.f;
                            asm volatile("" : "+f"(d[0][i]));
                        }
                        if (real) mbar_wait_nt(bs + 32, 0);
#pragma unroll
                        for (int i = 2 * RA; i < 8; i++) w[i] = ldsm4t(wa + 3 * 16384 + i * 2048);
#pragma unroll
                        for (int i = RA; i < 4; i++) {
                            mma16816(d[(i - RA) * 2], w[2 * i].x, w[2 * i].y, w[2 * i].z, w[2 * i].w, xf[i].x, xf[i].y);
                            mma16816(d[(i - RA) * 2 + 1], w[2 * i + 1].x, w[2 * i + 1].y, w[2 * i + 1].z, w[2 * i + 1].w, xf[i].z, xf[i].w);
                        }
                    }
                    STAMP(tid == 64, 22);
                    float e[4];
#pragma unroll
                    for (int i = 0; i < 4; i++) e[i] = (t & 2) ? d[i][2] : d[i][0];
                    red_out(dst, RA == 3 ? e[0] + e[1] : ((e[0] + e[1]) + e[2]) + e[3], g, real);
                    STAMP(tid == 64, 13);
                    if (real) asm volatile("exit;");
                } else if (step >= 2) {
                    uint2 bf[16];
                    tall_prep(bf, sb + SM_P, warp, g, t);
                    if (step & 1) mbar_wait(sb + SM_BAR + BAR_S + (warp >> 1) * 8, 0);
                    LAND(tid == 64, 17408 + 3 * 128 + j);
                    gemv_tall(sb + SM_SQ, bf, red + 512, warp, g, t);
                    tall_finish(red + 512, G.ctx + ((tid >> 5) & 1) * 4096 + 32 * j + (tid & 31), tid, tag, 0, (step & 1) ? 64 : 0);
                    STAMP(tid == 0, 12);
                } else {
                    const int b = step;
                    const int hm = min(h, 31), bh = 32 * b + hm;
                    wait_ticket(smem + SM_BAR + W_PROG, min((bh + 1) * 128 + LAGT, NT + YLATE + max(hm - 27, 0) * YSL));
                    __syncwarp();
                    float* rb = red + b * 256;
                    combineA(G, bh, qd, tag, rb, tid, smem + SM_BAR + W_PROG);
                    {
                        if (tid < 32)
                            st_relaxed32(G.o + bh * 128 + 32 * qd + tid, tagw((rb[tid] + rb[32 + tid]) + (rb[64 + tid] + rb[96 + tid]), tag));
                        STAMP(tid == 0, 9 + 2 * b);
                    }
                }
            }
        }
    }
}

typedef CUresult (*EncodeFn)(CUtensorMap*, CUtensorMapDataType, cuuint32_t, void*, const cuuint64_t*, const cuuint64_t*,
                             const cuuint32_t*, const cuuint32_t*, CUtensorMapInterleave, CUtensorMapSwizzle,
                             CUtensorMapL2promotion, CUtensorMapFloatOOBfill);

}

extern "C" void kernel_launch(void* const* d_in, const int* in_sizes, int n_in, void* d_out, int out_size) {
    (void)in_sizes; (void)n_in; (void)out_size;
    static EncodeFn encode = nullptr;
    static void* scratch = nullptr;
    if (!encode) {
        void* fn = nullptr;
        cudaDriverEntryPointQueryResult st;
        cudaGetDriverEntryPoint("cuTensorMapEncodeTiled", &fn, cudaEnableDefault, &st);
        encode = (EncodeFn)fn;
        cudaGetSymbolAddress(&scratch, g_raw);
        cudaFuncSetAttribute(fused_decode_kernel, cudaFuncAttributeMaxDynamicSharedMemorySize, SM_TOTAL);
    }
    Ptrs P;
    Maps M;
    auto mk = [&](CUtensorMap* m, void* ptr, cuuint64_t cols, cuuint64_t rows, cuuint32_t bc, cuuint32_t br, CUtensorMapSwizzle sw,
                  CUtensorMapL2promotion promo) {
        const cuuint64_t gdim[2] = {cols, rows};
        const cuuint64_t gstr[1] = {cols * 2};
        const cuuint32_t box[2] = {bc, br};
        const cuuint32_t estr[2] = {1, 1};
        encode(m, CU_TENSOR_MAP_DATA_TYPE_BFLOAT16, 2, ptr, gdim, gstr, box, estr, CU_TENSOR_MAP_INTERLEAVE_NONE, sw,
               promo, CU_TENSOR_MAP_FLOAT_OOB_FILL_NONE);
    };
    mk(&M.m_wq, d_in[3], 4096, 512, 32, 256, CU_TENSOR_MAP_SWIZZLE_64B, CU_TENSOR_MAP_L2_PROMOTION_NONE);
    auto mk3 = [&](CUtensorMap* m, void* ptr, cuuint64_t cols, cuuint64_t rows, cuuint32_t br, cuuint32_t bb) {
        const cuuint64_t gdim[3] = {64, rows, cols / 64};
        const cuuint64_t gstr[2] = {cols * 2, 128};
        const cuuint32_t box[3] = {64, br, bb};
        const cuuint32_t estr[3] = {1, 1, 1};
        encode(m, CU_TENSOR_MAP_DATA_TYPE_BFLOAT16, 3, ptr, gdim, gstr, box, estr, CU_TENSOR_MAP_INTERLEAVE_NONE,
               CU_TENSOR_MAP_SWIZZLE_128B, CU_TENSOR_MAP_L2_PROMOTION_L2_256B, CU_TENSOR_MAP_FLOAT_OOB_FILL_NONE);
    };
    mk3(&M.m_v, d_in[2], 128, 524288, 64, 2);
    mk(&M.m_uv[0], d_in[9], 4096, 512, 32, PV, CU_TENSOR_MAP_SWIZZLE_64B, CU_TENSOR_MAP_L2_PROMOTION_NONE);
    mk(&M.m_uv[1], d_in[9], 4096, 512, 32, PV, CU_TENSOR_MAP_SWIZZLE_64B, (CUtensorMapL2promotion)VPROMO);
    mk(&M.m_w[0], d_in[4], 512, 4096, 64, PR, CU_TENSOR_MAP_SWIZZLE_128B, (CUtensorMapL2promotion)WPROMO);
    mk(&M.m_w[1], d_in[10], 512, 4096, 64, PR, CU_TENSOR_MAP_SWIZZLE_128B, (CUtensorMapL2promotion)WPROMO);
    mk(&M.m_ckv, d_in[6], 512, 16384, 64, 64, CU_TENSOR_MAP_SWIZZLE_128B, CU_TENSOR_MAP_L2_PROMOTION_L2_256B);
    mk(&M.m_wqB, d_in[7], 4096, 512, 32, 256, CU_TENSOR_MAP_SWIZZLE_64B, CU_TENSOR_MAP_L2_PROMOTION_NONE);
    mk(&M.m_wuk, d_in[8], 4096, 512, 128, 128, CU_TENSOR_MAP_SWIZZLE_NONE, CU_TENSOR_MAP_L2_PROMOTION_L2_256B);
    P.xA = (const __nv_bfloat16*)d_in[0];
    P.K = (const __nv_bfloat16*)d_in[1];
    P.xB = (const __nv_bfloat16*)d_in[5];
    P.out = (__nv_bfloat16*)d_out;
    P.g = (Scratch*)scratch;
    cudaLaunchConfig_t cfg = {};
    cfg.gridDim = dim3(GRID);
    cfg.blockDim = dim3(NTHREADS);
    cfg.dynamicSmemBytes = SM_TOTAL;
    cfg.stream = cudaStreamPerThread;
    cudaLaunchAttribute attr;
    attr.id = cudaLaunchAttributeCooperative;
    attr.val.cooperative = 1;
    cfg.attrs = &attr;
    cfg.numAttrs = 1;
    cudaLaunchKernelEx(&cfg, fused_decode_kernel, P, M);
}
```

```cpp
#include <cuda_runtime.h>
#include <cuda_bf16.h>
#include <cuda.h>
#include <stdint.h>

namespace {

constexpr int NT       = 8192;
constexpr int GRID     = 132;
constexpr int NB_CTA   = 16;
constexpr int NA_CTA   = GRID - NB_CTA;
constexpr int NWORK    = 3;
#define YV 292
#define DV 56
#define YW 407
#define DW 68
#define DL 6
#define YX 150
#define YB 582
#define YP 605
#define XRV 330
#define TV 3200
#define PFB 8192
#define LAGT 1060
#define YLATE 120
#define YSL 70
#define YO 450
#define YOS 40
#define TUV (43 * 128)
#define XPK 80
#define FRZ 60
#define QDELAY 500
constexpr int NEARX = 400;
constexpr int JE0   = 112;
constexpr int HCLR  = 26;
constexpr int BINFL = 2;
constexpr int NSTATIC  = NA_CTA * NWORK;
constexpr unsigned DRAWS = (NT - NSTATIC) + GRID * NWORK;
static_assert(52 * 128 + LAGT + 300 <= NT && TUV + 10 * 128 <= NT, "wait_prog thresholds must be reachable");
constexpr int NTHREADS = 256;
constexpr float SCALE = 0.08838834764831845f, LOG2E = 1.4426950408889634f;
constexpr unsigned SPIN_LIMIT = 1u << 22;

constexpr int SM_SLOT  = 0;
constexpr int SM_QA    = 196608;
constexpr int SM_P     = SM_QA + 16384;
constexpr int SM_RED1  = SM_P + 4096;
constexpr int SM_RED2  = SM_RED1 + 2048;
constexpr int SM_VEC   = SM_RED2 + 4096;
constexpr int SM_BAR   = SM_VEC + 3072;
constexpr int SM_TOTAL = SM_BAR + 352;
constexpr int V_X    = 512;
constexpr int BAR_FULL = 0;
constexpr int BAR_PDONE= 48;
constexpr int BAR_BDONE= 56;
constexpr int BAR_QABS = 72;
constexpr int BAR_BFULL= 80;
constexpr int BAR_BEMPTY=120;
constexpr int BAR_WFREE= 160;
constexpr int BAR_W    = 168;
constexpr int BAR_S    = 192;
constexpr int BAR_Q    = 264;
constexpr int W_EPOCH  = 328;
constexpr int W_PROG   = 336;
constexpr int SM_WQ = 3 * 32768, SM_WQB = 4 * 32768, SM_WUK = 5 * 32768;
constexpr int SM_SQ = 3 * 32768;
constexpr int XSTR = 1024 + 16;

struct __align__(128) Cnt { unsigned v; unsigned pad[31]; };
struct __align__(128) Scratch {
    Cnt epoch, ticket, cntQabs, cntB;
    float qA[64 * 128], qB[64 * 128];
    __nv_bfloat16 qabs[2 * 32 * 512];
    float  partO[NT * 128];
    float2 partML[NT * 4];
    float  bpart[NB_CTA * 32 * 512];
    float2 bml[NB_CTA * 32];
    float  ctx[32 * 4 * 2 * 128];
    float  o[2 * 4096];
};
__device__ __align__(128) unsigned char g_raw[sizeof(Scratch)];

#define STAMP(cond, i) do {} while (0)
#define LAND(cond, i) do {} while (0)

__device__ __forceinline__ void mbar_init(uint32_t bar, int cnt) {
    asm volatile("mbarrier.init.shared::cta.b64 [%0], %1;" ::"r"(bar), "r"(cnt) : "memory");
}
__device__ __forceinline__ void mbar_expect_tx(uint32_t bar, uint32_t bytes) {
    asm volatile("mbarrier.arrive.expect_tx.shared::cta.b64 _, [%0], %1;" ::"r"(bar), "r"(bytes) : "memory");
}
__device__ __forceinline__ void mbar_arrive(uint32_t bar) {
    asm volatile("mbarrier.arrive.shared::cta.b64 _, [%0];" ::"r"(bar) : "memory");
}
__device__ __forceinline__ void mbar_wait(uint32_t bar, uint32_t parity) {
    unsigned it = 0;
    while (true) {
        uint32_t ok;
        asm volatile("{\n.reg .pred p;\nmbarrier.try_wait.parity.shared::cta.b64 p, [%1], %2;\nselp.u32 %0, 1, 0, p;\n}\n"
                     : "=r"(ok) : "r"(bar), "r"(parity) : "memory");
        if (ok) break;
        if (++it > SPIN_LIMIT) __trap();
    }
}
__device__ __forceinline__ void mbar_wait_nt(uint32_t bar, uint32_t parity) {
#pragma unroll 1
    for (unsigned it = 0; it < SPIN_LIMIT; it++) {
        uint32_t ok;
        asm volatile("{\n.reg .pred p;\nmbarrier.try_wait.parity.shared::cta.b64 p, [%1], %2;\nselp.u32 %0, 1, 0, p;\n}\n"
                     : "=r"(ok) : "r"(bar), "r"(parity) : "memory");
        if (ok) break;
    }
}
__device__ __forceinline__ bool mbar_test(uint32_t bar, uint32_t parity) {
    uint32_t ok;
    asm volatile("{\n.reg .pred p;\nmbarrier.test_wait.parity.shared::cta.b64 p, [%1], %2;\nselp.u32 %0, 1, 0, p;\n}\n"
                 : "=r"(ok) : "r"(bar), "r"(parity) : "memory");
    return ok;
}
__device__ __forceinline__ void bulk_load(uint32_t dst, const void* src, uint32_t bytes, uint32_t bar, uint64_t pol) {
    asm volatile("cp.async.bulk.shared::cluster.global.mbarrier::complete_tx::bytes.L2::cache_hint [%0], [%1], %2, [%3], %4;"
                 ::"r"(dst), "l"(src), "r"(bytes), "r"(bar), "l"(pol) : "memory");
}
__device__ __forceinline__ void bulk_load_nohint(uint32_t dst, const void* src, uint32_t bytes, uint32_t bar) {
    asm volatile("cp.async.bulk.shared::cluster.global.mbarrier::complete_tx::bytes [%0], [%1], %2, [%3];"
                 ::"r"(dst), "l"(src), "r"(bytes), "r"(bar) : "memory");
}
__device__ __forceinline__ void tma_2d(uint32_t dst, const CUtensorMap* map, int c0, int c1, uint32_t bar, uint64_t pol) {
    asm volatile("cp.async.bulk.tensor.2d.shared::cluster.global.mbarrier::complete_tx::bytes.L2::cache_hint [%0], [%1, {%3, %4}], [%2], %5;"
                 ::"r"(dst), "l"(map), "r"(bar), "r"(c0), "r"(c1), "l"(pol) : "memory");
}
__device__ __forceinline__ void tma_3d(uint32_t dst, const CUtensorMap* map, int c1, int c2, uint32_t bar, uint64_t pol) {
    asm volatile("cp.async.bulk.tensor.3d.shared::cluster.global.mbarrier::complete_tx::bytes.L2::cache_hint [%0], [%1, {%3, %4, %5}], [%2], %6;"
                 ::"r"(dst), "l"(map), "r"(bar), "r"(0), "r"(c1), "r"(c2), "l"(pol) : "memory");
}
__device__ __forceinline__ void wait_prog(const unsigned char* smem_word, unsigned th) {
    unsigned it = 0;
    while (*(volatile const unsigned*)(smem_word + 8) + NSTATIC < th) {
        __nanosleep(60);
        if (++it > SPIN_LIMIT) __trap();
    }
}
__device__ __forceinline__ uint32_t now_ns() {
    uint32_t t;
    asm volatile("mov.u32 %0, %globaltimer_lo;" : "=r"(t) :: "memory");
    return t;
}
__device__ __forceinline__ void note_draw(unsigned char* smem_word, unsigned raw) {
    const uint32_t a = (uint32_t)__cvta_generic_to_shared(smem_word);
    asm volatile("st.volatile.u32 [%0], %1;" ::"l"(smem_word + 8), "r"(raw) : "memory");
    const uint32_t now = now_ns();
    if ((int)raw < NT - NSTATIC - FRZ) asm volatile("st.volatile.shared.v2.u32 [%0], {%1, %2};" ::"r"(a), "r"(raw), "r"(now) : "memory");
}
__device__ __forceinline__ void wait_ticket(const unsigned char* smem_word, int th) {
    wait_prog(smem_word, min(th, NT - NEARX));
    uint32_t tk, t0;
#pragma unroll 1
    for (unsigned it = 0; it < SPIN_LIMIT; it++) {
        asm volatile("ld.volatile.shared.v2.u32 {%0, %1}, [%2];" : "=r"(tk), "=r"(t0) : "r"((uint32_t)__cvta_generic_to_shared(smem_word)) : "memory");
        if ((int)(now_ns() - t0) >= (th - NSTATIC - (int)tk) * 10) break;
        __nanosleep(20);
    }
}
__device__ __forceinline__ bool mbar_wait_for(uint32_t bar, uint32_t parity, int n) {
    uint32_t c0, c;
    asm volatile("mov.u32 %0, %%clock;" : "=r"(c0) :: "memory");
    do {
        if (mbar_test(bar, parity)) return true;
        asm volatile("mov.u32 %0, %%clock;" : "=r"(c) :: "memory");
    } while ((int)(c - c0) < n);
    return false;
}
__device__ __forceinline__ bool elect_one() {
    uint32_t p;
    asm volatile("{\n.reg .pred p;\nelect.sync _|p, 0xffffffff;\nselp.u32 %0, 1, 0, p;\n}\n" : "=r"(p));
    return p;
}
__device__ __forceinline__ void fence_proxy_async() { asm volatile("fence.proxy.async;" ::: "memory"); }
__device__ __forceinline__ void named_bar(int id, int n) { asm volatile("bar.sync %0, %1;" ::"r"(id), "r"(n) : "memory"); }

__device__ __forceinline__ uint4 lds128(uint32_t a) {
    uint4 v;
    asm volatile("ld.shared.v4.u32 {%0,%1,%2,%3}, [%4];" : "=r"(v.x), "=r"(v.y), "=r"(v.z), "=r"(v.w) : "r"(a));
    return v;
}
__device__ __forceinline__ uint4 ldsm4(uint32_t a) {
    uint4 v;
    asm volatile("ldmatrix.sync.aligned.m8n8.x4.shared.b16 {%0,%1,%2,%3}, [%4];" : "=r"(v.x), "=r"(v.y), "=r"(v.z), "=r"(v.w) : "r"(a));
    return v;
}
__device__ __forceinline__ uint4 ldsm4t(uint32_t a) {
    uint4 v;
    asm volatile("ldmatrix.sync.aligned.m8n8.x4.trans.shared.b16 {%0,%1,%2,%3}, [%4];" : "=r"(v.x), "=r"(v.y), "=r"(v.z), "=r"(v.w) : "r"(a));
    return v;
}
__device__ __forceinline__ uint2 lds64(uint32_t a) {
    uint2 v;
    asm volatile("ld.shared.v2.u32 {%0,%1}, [%2];" : "=r"(v.x), "=r"(v.y) : "r"(a));
    return v;
}
__device__ __forceinline__ uint4 ld_relaxed128(const void* p) {
    uint4 v;
    asm volatile("ld.relaxed.gpu.global.v4.u32 {%0,%1,%2,%3}, [%4];" : "=r"(v.x), "=r"(v.y), "=r"(v.z), "=r"(v.w) : "l"(p) : "memory");
    return v;
}
__device__ __forceinline__ uint2 ld_relaxed64(const void* p) {
    uint2 v;
    asm volatile("ld.relaxed.gpu.global.v2.u32 {%0,%1}, [%2];" : "=r"(v.x), "=r"(v.y) : "l"(p) : "memory");
    return v;
}
__device__ __forceinline__ uint32_t ld_relaxed32(const void* p) {
    uint32_t v;
    asm volatile("ld.relaxed.gpu.global.u32 %0, [%1];" : "=r"(v) : "l"(p) : "memory");
    return v;
}
__device__ __forceinline__ uint32_t ld_acquire32(const void* p) {
    uint32_t v;
    asm volatile("ld.acquire.gpu.global.u32 %0, [%1];" : "=r"(v) : "l"(p) : "memory");
    return v;
}
__device__ __forceinline__ void st_relaxed128(void* p, uint32_t a, uint32_t b, uint32_t c, uint32_t d) {
    asm volatile("st.relaxed.gpu.global.v4.u32 [%0], {%1,%2,%3,%4};" ::"l"(p), "r"(a), "r"(b), "r"(c), "r"(d) : "memory");
}
__device__ __forceinline__ void red_release(unsigned* p) {
    asm volatile("red.release.gpu.global.add.u32 [%0], 1;" ::"l"(p) : "memory");
}
__device__ __forceinline__ void wait_counter(const unsigned* p, unsigned target, unsigned ns) {
    unsigned it = 0;
    while ((int)(ld_acquire32(p) - target) < 0) {
        __nanosleep(ns);
        if (++it > SPIN_LIMIT) __trap();
    }
}
__device__ __forceinline__ uint32_t prmt(uint32_t a, uint32_t b, uint32_t s) {
    uint32_t d;
    asm("prmt.b32 %0, %1, %2, %3;" : "=r"(d) : "r"(a), "r"(b), "r"(s));
    return d;
}
__device__ __forceinline__ uint32_t pack_bf16(float lo, float hi) {
    uint32_t d;
    asm("cvt.rn.bf16x2.f32 %0, %1, %2;" : "=r"(d) : "f"(hi), "f"(lo));
    return d;
}
__device__ __forceinline__ float ex2(float x) {
    float y;
    asm("ex2.approx.ftz.f32 %0, %1;" : "=f"(y) : "f"(x));
    return y;
}
__device__ __forceinline__ float bf_lo(uint32_t v) { return __uint_as_float(v << 16); }
__device__ __forceinline__ float bf_hi(uint32_t v) { return __uint_as_float(v & 0xffff0000u); }
__device__ __forceinline__ void scale_scores(float& a, float& b) {
    uint32_t p = pack_bf16(a, b);
    p = pack_bf16(bf_lo(p) * SCALE, bf_hi(p) * SCALE);
    a = bf_lo(p); b = bf_hi(p);
}
__device__ __forceinline__ uint32_t tagw(float v, uint32_t tag) {
    uint32_t d;
    asm("lop3.b32 %0, %1, 0xfffffffe, %2, 0xEA;" : "=r"(d) : "r"(__float_as_uint(v)), "r"(tag));
    return d;
}
__device__ __forceinline__ uint32_t bad2(uint32_t x, uint32_t y, uint32_t tag) {
    uint32_t d;
    asm("lop3.b32 %0, %1, %2, %3, 0x7E;" : "=r"(d) : "r"(x), "r"(y), "r"(tag));
    return d;
}
__device__ __forceinline__ uint32_t bad4(const uint4& v, uint32_t tag) { return bad2(v.x, v.y, tag) | bad2(v.z, v.w, tag); }
__device__ __forceinline__ void ld_relaxed128_if(uint4& v, const void* p, uint32_t c) {
    asm volatile("{\n.reg .pred p;\nsetp.ne.u32 p, %5, 0;\n@p ld.relaxed.gpu.global.v4.u32 {%0,%1,%2,%3}, [%4];\n}\n"
                 : "+r"(v.x), "+r"(v.y), "+r"(v.z), "+r"(v.w) : "l"(p), "r"(c) : "memory");
}
__device__ __forceinline__ void ld_relaxed64_if(uint2& v, const void* p, uint32_t c) {
    asm volatile("{\n.reg .pred p;\nsetp.ne.u32 p, %3, 0;\n@p ld.relaxed.gpu.global.v2.u32 {%0,%1}, [%2];\n}\n"
                 : "+r"(v.x), "+r"(v.y) : "l"(p), "r"(c) : "memory");
}
__device__ __forceinline__ void st_relaxed32(void* p, uint32_t a) {
    asm volatile("st.relaxed.gpu.global.u32 [%0], %1;" ::"l"(p), "r"(a) : "memory");
}
__device__ __forceinline__ void red_out(uint32_t* word, float v, int col, uint32_t go) {
    const uint32_t pk = (col & 1) ? pack_bf16(-0.f, v) : pack_bf16(v, -0.f);
    asm volatile("{\n.reg .pred p;\nsetp.ne.u32 p, %2, 0;\n@p red.relaxed.gpu.global.add.noftz.bf16x2 [%0], %1;\n}\n"
                 ::"l"(word), "r"(pk), "r"(go) : "memory");
}
__device__ __forceinline__ void mma16816(float (&c)[4], uint32_t a0, uint32_t a1, uint32_t a2, uint32_t a3,
                                         uint32_t b0, uint32_t b1) {
    asm("mma.sync.aligned.m16n8k16.row.col.f32.bf16.bf16.f32 {%0,%1,%2,%3}, {%4,%5,%6,%7}, {%8,%9}, {%0,%1,%2,%3};"
        : "+f"(c[0]), "+f"(c[1]), "+f"(c[2]), "+f"(c[3])
        : "r"(a0), "r"(a1), "r"(a2), "r"(a3), "r"(b0), "r"(b1));
}
__device__ __forceinline__ uint64_t make_desc(uint32_t addr) {
    return (uint64_t)((addr & 0x3FFFF) >> 4) | ((uint64_t)1 << 16) | ((uint64_t)64 << 32) | ((uint64_t)1 << 62);
}
template <int TRANS_A>
__device__ __forceinline__ void wgmma_n32(float (&d)[16], uint64_t da, uint64_t db, int scale_d) {
    asm volatile("{\n.reg .pred p;\nsetp.ne.b32 p, %18, 0;\n"
                 "wgmma.mma_async.sync.aligned.m64n32k16.f32.bf16.bf16 "
                 "{%0,%1,%2,%3,%4,%5,%6,%7,%8,%9,%10,%11,%12,%13,%14,%15}, %16, %17, p, 1, 1, %19, 0;\n}\n"
                 : "+f"(d[0]), "+f"(d[1]), "+f"(d[2]), "+f"(d[3]), "+f"(d[4]), "+f"(d[5]), "+f"(d[6]), "+f"(d[7]),
                   "+f"(d[8]), "+f"(d[9]), "+f"(d[10]), "+f"(d[11]), "+f"(d[12]), "+f"(d[13]), "+f"(d[14]), "+f"(d[15])
                 : "l"(da), "l"(db), "r"(scale_d), "n"(TRANS_A));
}
__device__ __forceinline__ void wg_fence()  { asm volatile("wgmma.fence.sync.aligned;" ::: "memory"); }
__device__ __forceinline__ void wg_commit() { asm volatile("wgmma.commit_group.sync.aligned;" ::: "memory"); }
template <int N> __device__ __forceinline__ void wg_wait() { asm volatile("wgmma.wait_group.sync.aligned %0;" ::"n"(N) : "memory"); }

__device__ __forceinline__ void issue_tall(uint32_t dst, const CUtensorMap* map, int col, int row, uint32_t bar, uint64_t pol) {
    tma_2d(dst, map, col, row, bar, pol);
    tma_2d(dst + 16384, map, col, row + 256, bar, pol);
}
__device__ __forceinline__ void tall_prep(uint2 (&bf)[16], uint32_t xbase, int w4, int g, int t) {
    const uint32_t xp = xbase + ((g >> 1) & 1) * 1024 + w4 * 256 + (t >> 1) * 8;
    const uint32_t sel = (g & 1) ? ((t & 1) ? 0x3244u : 0x1044u) : ((t & 1) ? 0x4432u : 0x4410u);
#pragma unroll
    for (int i = 0; i < 16; i++) {
        const uint2 xw = lds64(xp + i * 16);
        bf[i] = make_uint2(prmt(xw.x, 0, sel), prmt(xw.y, 0, sel));
    }
}
__device__ __forceinline__ void gemv_tall(uint32_t wbase, const uint2 (&bf)[16], float* red, int w4, int g, int t) {
    const uint32_t wu = wbase + (128 * w4 + (t & 1) + 4 * (t >> 1)) * 64 + (((g >> 1) ^ (t & 2)) << 4) + (g & 1) * 8;
    const uint32_t wv = (wu + 128) ^ 16;
    float a[4][4];
#pragma unroll
    for (int i = 0; i < 16; i++) (&a[0][0])[i] = 0.f;
#pragma unroll
    for (int i = 0; i < 16; i++) {
        const uint2 u = lds64(wu + i * 512), v = lds64(wv + i * 512);
        mma16816(a[i & 3], u.x, u.y, v.x, v.y, bf[i].x, bf[i].y);
    }
    if (t < 2)
        *(float4*)(red + (w4 * 2 + t) * 32 + 4 * g) =
            make_float4((a[0][0] + a[1][0]) + (a[2][0] + a[3][0]), (a[0][1] + a[1][1]) + (a[2][1] + a[3][1]),
                        (a[0][2] + a[1][2]) + (a[2][2] + a[3][2]), (a[0][3] + a[1][3]) + (a[2][3] + a[3][3]));
}
__device__ __forceinline__ void tall_finish(const float* red, float* dst, int tid, uint32_t tag, int lo = 0, int hi = 64) {
    named_bar(1, 128);
    if (tid >= lo && tid < hi) {
        st_relaxed32(dst, tagw((red[tid] + red[64 + tid]) + (red[128 + tid] + red[192 + tid]), tag));
    }
}

__device__ __forceinline__ void combineA(Scratch& G, int bh, int dq, uint32_t tag, float* red, int tid, const unsigned char* prog) {
    const int r = tid >> 3, c4 = tid & 7, w4 = tid >> 5, lane = tid & 31;
    const float2* ml = G.partML + (bh * 128 + r) * 4;
    const float* po = G.partO + (size_t)(bh * 128 + r) * 128 + dq * 32 + c4 * 4;
    uint2 m[8];
    uint4 o[8];
    uint32_t bad[8];
    STAMP(tid == 0 && bh >= 32, 28);
#pragma unroll
    for (int k = 0; k < 8; k++) m[k] = ld_relaxed64(ml + 64 * k);
#pragma unroll
    for (int k = 0; k < 8; k++) {
        o[k] = make_uint4(~tag, ~tag, ~tag, ~tag);
        ld_relaxed128_if(o[k], po + (size_t)k * 16 * 128, bh < 60);
    }
    unsigned it = 0;
    while (true) {
        uint32_t any = 0;
#pragma unroll
        for (int k = 0; k < 8; k++) { bad[k] = bad2(m[k].x, m[k].y, tag) & 1u; any |= bad[k]; }
        if (!__any_sync(~0u, any)) break;
#pragma unroll
        for (int k = 0; k < 8; k++) ld_relaxed64_if(m[k], ml + 64 * k, bad[k]);
        if (++it > SPIN_LIMIT) __trap();
    }
    STAMP(tid == 0 && bh >= 32, 30);
    STAMP(tid == 0 && bh >= 32, 19);
    float M = fmaxf(fmaxf(fmaxf(__uint_as_float(m[0].x), __uint_as_float(m[1].x)), fmaxf(__uint_as_float(m[2].x), __uint_as_float(m[3].x))),
                    fmaxf(fmaxf(__uint_as_float(m[4].x), __uint_as_float(m[5].x)), fmaxf(__uint_as_float(m[6].x), __uint_as_float(m[7].x))));
    M = fmaxf(M, __shfl_xor_sync(~0u, M, 8));
    M = fmaxf(M, __shfl_xor_sync(~0u, M, 16));
    float wgt[8], L = 0.f;
#pragma unroll
    for (int k = 0; k < 8; k++) {
        wgt[k] = ex2(__uint_as_float(m[k].x) - M);
        L = fmaf(wgt[k], __uint_as_float(m[k].y), L);
    }
    L += __shfl_xor_sync(~0u, L, 8);
    L += __shfl_xor_sync(~0u, L, 16);
    if (lane == 0) { red[128 + w4] = M; red[132 + w4] = L; }
    named_bar(1, 128);
    {
        const float4 Mw = *(float4*)(red + 128), Lw = *(float4*)(red + 132);
        const float Mx = fmaxf(fmaxf(Mw.x, Mw.y), fmaxf(Mw.z, Mw.w));
        const float Lt = (ex2(Mw.x - Mx) * Lw.x + ex2(Mw.y - Mx) * Lw.y) + (ex2(Mw.z - Mx) * Lw.z + ex2(Mw.w - Mx) * Lw.w);
        const float f = ex2(M - Mx) / Lt;
#pragma unroll
        for (int k = 0; k < 8; k++) wgt[k] *= f;
    }
    STAMP(tid == 0 && bh >= 32, 23);
    if (bh >= 60) wait_ticket(prog, NT + YO + (bh - 63) * YOS);
    while (true) {
        uint32_t any = 0;
#pragma unroll
        for (int k = 0; k < 8; k++) { bad[k] = bad4(o[k], tag) & 1u; any |= bad[k]; }
        if (!__any_sync(~0u, any)) break;
#pragma unroll
        for (int k = 0; k < 8; k++) ld_relaxed128_if(o[k], po + (size_t)k * 16 * 128, bad[k]);
        if (++it > SPIN_LIMIT) __trap();
    }
    STAMP(tid == 0 && bh >= 32, 31);
    float a0 = 0.f, a1 = 0.f, a2 = 0.f, a3 = 0.f, b0 = 0.f, b1 = 0.f, b2 = 0.f, b3 = 0.f;
#pragma unroll
    for (int k = 0; k < 8; k += 2) {
        a0 = fmaf(wgt[k], __uint_as_float(o[k].x), a0); b0 = fmaf(wgt[k + 1], __uint_as_float(o[k + 1].x), b0);
        a1 = fmaf(wgt[k], __uint_as_float(o[k].y), a1); b1 = fmaf(wgt[k + 1], __uint_as_float(o[k + 1].y), b1);
        a2 = fmaf(wgt[k], __uint_as_float(o[k].z), a2); b2 = fmaf(wgt[k + 1], __uint_as_float(o[k + 1].z), b2);
        a3 = fmaf(wgt[k], __uint_as_float(o[k].w), a3); b3 = fmaf(wgt[k + 1], __uint_as_float(o[k + 1].w), b3);
    }
    a0 += b0; a1 += b1; a2 += b2; a3 += b3;
#pragma unroll
    for (int s = 8; s <= 16; s <<= 1) {
        a0 += __shfl_xor_sync(~0u, a0, s);
        a1 += __shfl_xor_sync(~0u, a1, s);
        a2 += __shfl_xor_sync(~0u, a2, s);
        a3 += __shfl_xor_sync(~0u, a3, s);
    }
    if (lane < 8) *(float4*)(red + w4 * 32 + c4 * 4) = make_float4(a0, a1, a2, a3);
    named_bar(1, 128);
    STAMP(tid == 0 && bh >= 32, 24);
}

struct Ptrs {
    const __nv_bfloat16 *K, *xA, *xB;
    __nv_bfloat16* out;
    Scratch* g;
};
struct Maps { CUtensorMap m_wq, m_v, m_ckv, m_wqB, m_wuk, m_uv[2], m_w[2]; };

__global__ void __launch_bounds__(NTHREADS, 1)
fused_decode_kernel(const Ptrs P, const __grid_constant__ Maps M) {
    extern __shared__ __align__(1024) unsigned char smem[];
    const uint32_t sb = (uint32_t)__cvta_generic_to_shared(smem);
    uint64_t pol;
    asm("createpolicy.fractional.L2::evict_first.b64 %0, 1.0;" : "=l"(pol));
    asm volatile("{\n.reg .pred p;\nsetp.lt.u32 p, %3, 32;\n@p cp.async.bulk.prefetch.L2.global.L2::cache_hint [%0], %1, %2;\n}\n"
                 ::"l"((const char*)P.K + (blockIdx.x << 14)), "n"(PFB), "l"(pol), "r"(threadIdx.x) : "memory");
    if (threadIdx.x < 32 && elect_one()) {
        mbar_init(sb + SM_BAR + BAR_FULL, 1);
        mbar_init(sb + SM_BAR + BAR_W, 1);
        asm volatile("fence.mbarrier_init.release.cluster;" ::: "memory");
        if (blockIdx.x < NA_CTA) {
            mbar_expect_tx(sb + SM_BAR + BAR_FULL, 16384);
            bulk_load(sb + SM_SLOT, (const char*)P.K + (blockIdx.x << 14), 16384, sb + SM_BAR + BAR_FULL, pol);
        }
        if (blockIdx.x < 128) {
            mbar_expect_tx(sb + SM_BAR + BAR_W, 32768 + 4096);
            issue_tall(sb + SM_WQ, &M.m_wq, blockIdx.x * 32, 0, sb + SM_BAR + BAR_W, pol);
            bulk_load_nohint(sb + SM_P, P.xA, 2048, sb + SM_BAR + BAR_W);
            bulk_load_nohint(sb + SM_P + 2048, P.xB, 2048, sb + SM_BAR + BAR_W);
        }
    }
    const int tid = threadIdx.x, warp = __shfl_sync(~0u, tid >> 5, 0), lane = tid & 31;
    const int g = lane >> 2, t = lane & 3;
    const int cta = blockIdx.x;
    Scratch& G = *P.g;
    const bool isB = cta >= NA_CTA;
    const bool hasSlice = cta < 128;
    const int j = cta, h = j >> 2, qd = j & 3;
    const int mat = j >> 6, cg = j & 7, rg = (j >> 3) & 7;
    const bool late = j < JE0 || j >= 124;
    STAMP(tid == 32, 0);
    if (warp == 7) {
        __syncthreads();
        const uint32_t epoch = *(volatile uint32_t*)(smem + SM_BAR + W_EPOCH);
        const uint32_t tag = (epoch + 1) & 1;
        if (!isB) { mbar_wait(sb + SM_BAR + BAR_W, 0); __nanosleep(QDELAY); }
#pragma unroll 1
        for (int i = 0; i < 8; i++) {
            if (i == 4 && !isB) wait_prog(smem + SM_BAR + W_PROG, 16 * 128);
            if (i == 0 && isB) { mbar_wait(sb + SM_BAR + BAR_QABS, 0); __nanosleep(8000); }
            uint4 v[8];
            uint32_t bad[8];
#pragma unroll
            for (int k = 0; k < 8; k++) { bad[k] = 1; v[k] = make_uint4(0, 0, 0, 0); }
            unsigned it = 0;
            while (true) {
#pragma unroll
                for (int k = 0; k < 8; k++) ld_relaxed128_if(v[k], G.qA + (8 * i + k) * 128 + lane * 4, bad[k]);
                uint32_t any = 0;
#pragma unroll
                for (int k = 0; k < 8; k++) { bad[k] = bad4(v[k], tag) & 1u; any |= bad[k]; }
                if (!__any_sync(~0u, any)) break;
                __nanosleep(40);
                if (++it > SPIN_LIMIT) __trap();
            }
#pragma unroll
            for (int k = 0; k < 8; k++) {
                uint32_t* dst = (uint32_t*)(smem + SM_QA + (8 * i + k) * 256 + (lane >> 1) * 16 + (lane & 1) * 4);
                dst[0] = pack_bf16(__uint_as_float(v[k].x), __uint_as_float(v[k].y));
                dst[2] = pack_bf16(__uint_as_float(v[k].z), __uint_as_float(v[k].w));
            }
            __syncwarp();
            if (lane == 0) mbar_arrive(sb + SM_BAR + BAR_Q + i * 8);
            STAMP(lane == 0 && i == 0, 2);
        }
        STAMP(lane == 0, 21);
        if (hasSlice && lane == 0) {
            mbar_wait(sb + SM_BAR + BAR_PDONE, 0);
#pragma unroll 1
            for (int p = 0; p < 12; p++) {
                const bool uv = p < 4;
                const int r = uv ? p * 128 : (p - 4) * 64;
                if (!uv || late)
                    wait_ticket(smem + SM_BAR + W_PROG, NT + (uv ? YV + (p * DV >> 1) : YW + ((p - 4) * DW >> 1) + (p == 11 ? DL : 0)));
                STAMP(p == 4, 10);
                const uint32_t bar = sb + SM_BAR + BAR_S + (p < 11 ? p >> 1 : 6) * 8;
                if (!(p & 1) || p == 11) mbar_expect_tx(bar, p < 10 ? 16384 : 8192);
                tma_2d(sb + SM_SQ + p * 8192, uv ? &M.m_uv[late] : &M.m_w[mat], uv ? j * 32 : cg * 64,
                       uv ? r : (rg + 8 * (r >> 7)) * 128 + (r & 127), bar, pol);
            }
        }
    } else if (warp >= 4) {
        const int wi = warp - 4;
        const uint32_t slot = sb + SM_SLOT + wi * 32768;
        const uint32_t bar = sb + SM_BAR + BAR_FULL + wi * 16, barV = bar + 8;
        unsigned tk = wi * NA_CTA + cta;
        const int ev = wi;
        if (lane == 0) {
            if (wi) mbar_init(bar, 1);
            mbar_init(barV, 1);
            if (isB && wi == 0) {
                for (int s = 0; s < 5; s++) {
                    mbar_init(sb + SM_BAR + BAR_BFULL + s * 8, 1);
                    mbar_init(sb + SM_BAR + BAR_BEMPTY + s * 8, 4);
                }
            }
            asm volatile("fence.mbarrier_init.release.cluster;" ::: "memory");
        }
        __syncthreads();
        const uint32_t epoch = *(volatile uint32_t*)(smem + SM_BAR + W_EPOCH);
        const uint32_t tag = (epoch + 1) & 1;

        bool active = true;
        if (isB) {
            if (wi == 1 && lane == 0) {
                wait_counter(&G.cntQabs.v, (epoch + 1) * 128, 64);
                fence_proxy_async();
                mbar_expect_tx(sb + SM_BAR + BAR_QABS, 32768);
                bulk_load_nohint(sb + SM_SLOT + 5 * 32768, G.qabs + ((cta - NA_CTA) >> 3) * 16384, 32768, sb + SM_BAR + BAR_QABS);
            }
            if (wi == 0 && lane == 0) {
                const int ib = cta - NA_CTA;
                int s = 0, sl = 0; uint32_t ph = 1, phl = 0;
                for (int u = 0; u < 32; u++) {
                    if (u >= BINFL) {
                        mbar_wait(sb + SM_BAR + BAR_BFULL + sl * 8, phl);
                        LAND(true, 16384 + ib * 32 + u);
                        if (++sl == 5) { sl = 0; phl ^= 1; }
                    }
                    if (u == 3 && hasSlice) mbar_wait(sb + SM_BAR + BAR_WFREE, 0);
                    mbar_wait(sb + SM_BAR + BAR_BEMPTY + s * 8, ph);
                    const uint32_t fb = sb + SM_BAR + BAR_BFULL + s * 8;
                    const int row = (ib >> 3) * 8192 + ((u >> 1) * 8 + (ib & 7)) * 64;
                    mbar_expect_tx(fb, 32768);
                    for (int x = 0; x < 4; x++)
                        tma_2d(sb + SM_SLOT + s * 32768 + x * 8192, &M.m_ckv, ((u & 1) * 4 + x) * 64, row, fb, pol);
                    if (++s == 5) { s = 0; ph ^= 1; }
                }
            }
            __syncwarp();
            mbar_wait(sb + SM_BAR + BAR_BDONE, 0);
            if (lane == 0) tk = NSTATIC + atomicInc(&G.ticket.v, DRAWS - 1);
            tk = __shfl_sync(~0u, tk, 0);
            active = tk < NT;
        } else if (ev != 0) {
            __syncwarp();
            mbar_wait(sb + SM_BAR + BAR_W + (ev - 1) * 8, 0);
        }
        if (active) {
            if ((isB || ev != 0) && lane == 0) {
                mbar_expect_tx(bar, 16384);
                bulk_load(slot, (const char*)P.K + (size_t)tk * 16384, 16384, bar, pol);
            }
            const uint32_t kA = slot + g * 256 + t * 16 + (g & 1) * 64, kB = kA ^ 64;
            const uint32_t qo = t * 16 + ((g >> 1) & 1) * 64 + (g & 1) * 8;
            const uint32_t v0 = slot + 16384 + (2 * t) * 128 + ((g ^ (2 * t)) << 4), v1 = (v0 + 128) ^ 16;
            const uint32_t sl0 = (g & 1) ? 0x1044u : 0x4410u, sl1 = (g & 1) ? 0x3244u : 0x4432u;
            const uint32_t sa0 = (g & 2) ? 0x4444u : sl0, sa1 = (g & 2) ? 0x4444u : sl1;
            const uint32_t sb0 = (g & 2) ? sl0 : 0x4444u, sb1 = (g & 2) ? sl1 : 0x4444u;
            const int d0 = 64 * (t >> 1) + 8 * g + 4 * (t & 1);
            uint32_t ph = 0;
            while (true) {
                const uint32_t qa = sb + SM_QA + (tk >> 7) * 256 + qo;
                bool vout = false;
                if (XRV && lane == 0 && tk >= NT - XRV && !mbar_wait_for(bar, ph, TV)) {
                    mbar_expect_tx(barV, 16384);
                    tma_3d(slot + 16384, &M.m_v, tk * 64, 0, barV, pol);
                    vout = true;
                }
                if (XRV) __syncwarp();
                mbar_wait(bar, ph);
                LAND(lane == 0, tk);
                unsigned nxt = 0;
                if (lane == 0) {
                    if (!vout) {
                        mbar_expect_tx(barV, 16384);
                        tma_3d(slot + 16384, &M.m_v, tk * 64, 0, barV, pol);
                    }
                    asm volatile("atom.relaxed.gpu.global.inc.u32 %0, [%1], %2;" : "=r"(nxt) : "l"(&G.ticket.v), "r"(DRAWS - 1) : "memory");
                }
                __syncwarp();
                mbar_wait(sb + SM_BAR + BAR_Q + (tk >> 10) * 8, 0);
                STAMP(tid == 128 && tk < NSTATIC, 3);
                uint2 qf[4];
                qf[0] = lds64(qa); qf[1] = lds64(qa ^ 64); qf[2] = lds64(qa + 128); qf[3] = lds64((qa ^ 64) + 128);
                float c[8][4];
#pragma unroll
                for (int i = 0; i < 32; i++) (&c[0][0])[i] = 0.f;
#pragma unroll
                for (int s = 0; s < 4; s++)
#pragma unroll
                    for (int jj = 0; jj < 8; jj++) {
                        const uint4 u = lds128(((s & 1) ? kB : kA) + jj * 2048 + (s >> 1) * 128);
                        mma16816(c[jj], u.x, u.y, u.z, u.w, qf[s].x, qf[s].y);
                    }
                float sc[8];
#pragma unroll
                for (int jj = 0; jj < 8; jj++) sc[jj] = c[jj][0] + c[jj][3];
#pragma unroll
                for (int jj = 0; jj < 8; jj += 2) scale_scores(sc[jj], sc[jj + 1]);
                float m = fmaxf(fmaxf(fmaxf(sc[0], sc[1]), fmaxf(sc[2], sc[3])), fmaxf(fmaxf(sc[4], sc[5]), fmaxf(sc[6], sc[7])));
                m = fmaxf(m, __shfl_xor_sync(~0u, m, 5));
                m = fmaxf(m, __shfl_xor_sync(~0u, m, 8));
                m = fmaxf(m, __shfl_xor_sync(~0u, m, 16));
                const float ms = __uint_as_float(tagw(m * LOG2E, tag));
                uint32_t W0[4], W1[4];
                float l = 0.f;
#pragma unroll
                for (int i = 0; i < 4; i++) {
                    const uint32_t pp = pack_bf16(ex2(fmaf(sc[2 * i], LOG2E, -ms)), ex2(fmaf(sc[2 * i + 1], LOG2E, -ms)));
                    W0[i] = __shfl_sync(~0u, pp, 8 * t);
                    W1[i] = __shfl_sync(~0u, pp, 8 * t + 5);
                    l += bf_lo(pp) + bf_hi(pp);
                }
                l += __shfl_xor_sync(~0u, l, 5);
                l += __shfl_xor_sync(~0u, l, 8);
                l += __shfl_xor_sync(~0u, l, 16);
                if (lane == 0 || lane == 2)
                    st_relaxed128((char*)G.partML + tk * 32 + lane * 8, __float_as_uint(ms), tagw(l, tag), __float_as_uint(ms), tagw(l, tag));
                uint32_t pb[16][2];
#pragma unroll
                for (int i = 0; i < 16; i++) {
                    const uint32_t pw = (i & 1) ? W1[i >> 2] : W0[i >> 2];
                    pb[i][0] = prmt(pw, 0, (i & 2) ? sa1 : sa0);
                    pb[i][1] = prmt(pw, 0, (i & 2) ? sb1 : sb0);
                    asm volatile("" : "+r"(pb[i][0]), "+r"(pb[i][1]));
                }
                float* po = G.partO + (size_t)tk * 128 + d0;
                asm volatile("" : "+l"(po));
                if (lane == 0) note_draw(smem + SM_BAR + W_PROG, nxt);
                nxt += NSTATIC;
                if (nxt >= NT - XPK && nxt < NT && lane == 0) {
                    mbar_expect_tx(bar, 16384);
                    bulk_load(slot, (const char*)P.K + (size_t)nxt * 16384, 16384, bar, pol);
                }
                mbar_wait(barV, ph);
                LAND(lane == 0, 8192 + tk);
                ph ^= 1;
                if (nxt < NT - XPK && lane == 0) {
                    mbar_expect_tx(bar, 16384);
                    bulk_load(slot, (const char*)P.K + (size_t)nxt * 16384, 16384, bar, pol);
                }
                __syncwarp();
                float acc[2][4][4];
#pragma unroll
                for (int i = 0; i < 32; i++) (&acc[0][0][0])[i] = 0.f;
#pragma unroll
                for (int jj = 0; jj < 8; jj++)
#pragma unroll
                    for (int e = 0; e < 2; e++)
#pragma unroll
                        for (int hh = 0; hh < 2; hh++) {
                            const uint4 u = lds128((e ? v1 : v0) + jj * 1024 + hh * 8192);
                            mma16816(acc[hh][(jj & 1) * 2 + e], u.x, u.y, u.z, u.w, pb[2 * jj + e][0], pb[2 * jj + e][1]);
                        }
                float r4[4];
#pragma unroll
                for (int i = 0; i < 4; i++) {
                    const float x0 = (acc[0][0][i] + acc[0][1][i]) + (acc[0][2][i] + acc[0][3][i]);
                    const float x1 = (acc[1][0][i] + acc[1][1][i]) + (acc[1][2][i] + acc[1][3][i]);
                    r4[i] = (t & 2) ? x1 : x0;
                }
                st_relaxed128(po, tagw(r4[0], tag), tagw(r4[1], tag), tagw(r4[2], tag), tagw(r4[3], tag));
                nxt = __shfl_sync(~0u, nxt, 0);
                if (nxt >= NT) break;
                tk = nxt;
            }
            STAMP(lane == 0, 16 + wi);
        } else if (lane == 0) {
            note_draw(smem + SM_BAR + W_PROG, tk - NSTATIC);
        }
    } else {
        float* red = (float*)(smem + SM_RED2);
        if (tid == 32) {
            const uint32_t ep0 = ld_relaxed32(&G.epoch.v);
            for (int e = 0; e < 8; e++) mbar_init(sb + SM_BAR + BAR_Q + e * 8, 1);
            for (int e = 1; e < 10; e++) mbar_init(sb + SM_BAR + BAR_W + e * 8, 1);
            mbar_init(sb + SM_BAR + BAR_BDONE, 1);
            mbar_init(sb + SM_BAR + BAR_PDONE, 1);
            mbar_init(sb + SM_BAR + BAR_QABS, 1);
            mbar_init(sb + SM_BAR + BAR_WFREE, 1);
            asm volatile("fence.mbarrier_init.release.cluster;" ::: "memory");
            asm volatile("st.volatile.shared.v4.u32 [%0], {%1, %2, %1, %1};" ::"r"(sb + SM_BAR + W_PROG), "r"(0), "r"(now_ns()) : "memory");
            *(volatile uint32_t*)(smem + SM_BAR + W_EPOCH) = ep0;
        } else if (tid == 64) {
            asm volatile("prefetch.tensormap [%0];" ::"l"(&M.m_v) : "memory");
            asm volatile("prefetch.tensormap [%0];" ::"l"(&M.m_wqB) : "memory");
            asm volatile("prefetch.tensormap [%0];" ::"l"(&M.m_wuk) : "memory");
        }
        __syncthreads();
        const uint32_t epoch = *(volatile uint32_t*)(smem + SM_BAR + W_EPOCH);
        const uint32_t tag = (epoch + 1) & 1;
        STAMP(tid == 0, 14);

        if (hasSlice) {
            const uint32_t nt = tag ^ 1;
            const int qoff = ((tid >> 5) & 1) * 4096 + 32 * j + (tid & 31);
            if (tid < 64) {
                st_relaxed32(G.qA + qoff, nt); st_relaxed32(G.qB + qoff, nt);
                if (tid < 32) {
                    st_relaxed32(G.o + 32 * j + tid, nt); st_relaxed32(G.o + 4096 + 32 * j + tid, nt);
                    st_relaxed32(G.ctx + 32 * j + tid, nt); st_relaxed32(G.ctx + 4096 + 32 * j + tid, nt);
                }
            }
            if (tid >= 64 && tid < 72) st_relaxed32((uint32_t*)P.out + 8 * j + (tid - 64), 0);
            mbar_wait(sb + SM_BAR + BAR_W, 0);
            LAND(tid == 0, 17408 + 0 * 128 + j);
            if (tid == 96) {
                mbar_expect_tx(sb + SM_BAR + BAR_W + 8, 32768);
                issue_tall(sb + SM_WQB, &M.m_wqB, j * 32, 0, sb + SM_BAR + BAR_W + 8, pol);
            }
            __syncwarp();
            STAMP(tid == 0, 15);
            uint2 bf[16];
            tall_prep(bf, sb + SM_P, warp, g, t);
            gemv_tall(sb + SM_WQ, bf, (float*)(smem + SM_RED1), warp, g, t);
            tall_finish((float*)(smem + SM_RED1), G.qA + qoff, tid, tag, 0, h >= HCLR ? 32 : 64);
            STAMP(tid == 0, 1);
            tall_prep(bf, sb + SM_P + 2048, warp, g, t);
            mbar_wait(sb + SM_BAR + BAR_W + 8, 0);
            LAND(tid == 0, 17408 + 1 * 128 + j);
            if (tid == 96) {
                mbar_expect_tx(sb + SM_BAR + BAR_W + 16, 32768);
                tma_2d(sb + SM_WUK, &M.m_wuk, h * 128, qd * 128, sb + SM_BAR + BAR_W + 16, pol);
            }
            __syncwarp();
            gemv_tall(sb + SM_WQB, bf, red, warp, g, t);
            tall_finish(red, G.qB + qoff, tid, tag);
            if (tid == 96) mbar_arrive(sb + SM_BAR + BAR_WFREE);
            STAMP(tid == 0, 25);
            named_bar(1, 128);
            uint4 qf[4];
            {
                const float* qp = G.qB + ((g & 1) * 32 + h) * 128 + t * 8;
                uint4 v[8];
                unsigned it = 0;
                while (true) {
                    uint32_t bad = 0;
#pragma unroll
                    for (int i = 0; i < 8; i++) v[i] = ld_relaxed128(qp + (i >> 1) * 32 + (i & 1) * 4);
#pragma unroll
                    for (int i = 0; i < 8; i++) bad |= bad4(v[i], tag);
                    if (!__any_sync(~0u, bad & 1u)) break;
                    __nanosleep(100);
                    if (++it > SPIN_LIMIT) __trap();
                }
#pragma unroll
                for (int s = 0; s < 4; s++)
                    qf[s] = make_uint4(pack_bf16(__uint_as_float(v[2 * s].x), __uint_as_float(v[2 * s].y)),
                                       pack_bf16(__uint_as_float(v[2 * s].z), __uint_as_float(v[2 * s].w)),
                                       pack_bf16(__uint_as_float(v[2 * s + 1].x), __uint_as_float(v[2 * s + 1].y)),
                                       pack_bf16(__uint_as_float(v[2 * s + 1].z), __uint_as_float(v[2 * s + 1].w)));
            }
            mbar_wait(sb + SM_BAR + BAR_W + 16, 0);
            LAND(tid == 0, 17408 + 2 * 128 + j);
#pragma unroll
            for (int jj = 0; jj < 2; jj++) {
                float c[4] = {0.f, 0.f, 0.f, 0.f};
#pragma unroll
                for (int s = 0; s < 4; s++) {
                    const uint32_t a = sb + SM_WUK + (32 * warp + 16 * jj + g) * 256 + (t + 4 * s) * 16;
                    const uint4 u = lds128(a), v = lds128(a + 2048);
                    mma16816(c, u.x, v.x, u.y, v.y, qf[s].x, qf[s].y);
                    mma16816(c, u.z, v.z, u.w, v.w, qf[s].z, qf[s].w);
                }
                const float val = (t & 2) ? ((t & 1) ? c[3] : c[2]) : ((t & 1) ? c[1] : c[0]);
                const int cc = 128 * qd + 32 * warp + 16 * jj + g + ((t & 2) ? 8 : 0);
                const int off = (cc >> 6) * 2048 + h * 64 + ((((cc & 63) >> 3) ^ (h & 7)) << 3) + (cc & 7);
                G.qabs[(t & 1) * 16384 + off] = __float2bfloat16(val);
            }
            named_bar(1, 128);
            if (tid == 0) red_release(&G.cntQabs.v);
            STAMP(tid == 0, 4);
            if (h >= HCLR) {
#pragma unroll
                for (int k = 0; k < 8; k++)
                    st_relaxed128(G.partO + (size_t)((32 + h) * 128 + 16 * k + (tid >> 3)) * 128 + qd * 32 + (tid & 7) * 4, nt, nt, nt, nt);
                if (tid < 64) st_relaxed128((char*)G.partML + ((32 + h) * 128 + qd * 32) * 32 + tid * 16, nt, nt, nt, nt);
                __threadfence();
                tall_finish((float*)(smem + SM_RED1), G.qA + qoff, tid, tag, 32, 64);
            }
        }

        if (isB) {
            const int ib = cta - NA_CTA;
            float acc[8][16];
#pragma unroll
            for (int i = 0; i < 8; i++)
#pragma unroll
                for (int k = 0; k < 16; k++) acc[i][k] = 0.f;
            float mrun[8], lrun[8];
#pragma unroll
            for (int i = 0; i < 8; i++) { mrun[i] = -INFINITY; lrun[i] = 0.f; }
            const uint64_t dQ = make_desc(sb + SM_SLOT + 5 * 32768);
            const uint64_t dP = make_desc(sb + SM_P);
            const uint32_t pst = sb + SM_P + (((lane >> 4) * 8 + (lane & 7)) * 128) + (((2 * warp + ((lane >> 3) & 1)) ^ (lane & 7)) << 4);
            mbar_wait(sb + SM_BAR + BAR_QABS, 0);
            STAMP(tid == 0, 5);
            int s0 = 0; uint32_t ph0 = 0;
            for (int it = 0; it < 16; it++) {
                int s1 = s0 + 1; uint32_t ph1 = ph0;
                if (s1 == 5) { s1 = 0; ph1 ^= 1; }
                const uint64_t dA0 = make_desc(sb + SM_SLOT + s0 * 32768), dA1 = make_desc(sb + SM_SLOT + s1 * 32768);
                float S[16];
                mbar_wait(sb + SM_BAR + BAR_BFULL + s0 * 8, ph0);
                mbar_wait(sb + SM_BAR + BAR_BFULL + s1 * 8, ph1);
                wg_fence();
#pragma unroll
                for (int k = 0; k < 32; k++) {
                    const uint64_t da = ((k < 16) ? dA0 : dA1) + (uint64_t)((((k >> 2) & 3) * 8192 + (k & 3) * 32) >> 4);
                    const uint64_t db = dQ + (uint64_t)(((k >> 2) * 4096 + (k & 3) * 32) >> 4);
                    wgmma_n32<0>(S, da, db, k > 0);
                }
                wg_commit();
                wg_wait<0>();
#pragma unroll
                for (int i = 0; i < 16; i++) S[i] *= SCALE;
                float mx[8];
#pragma unroll
                for (int i = 0; i < 8; i++) {
                    mx[i] = fmaxf(S[4 * (i >> 1) + (i & 1)], S[4 * (i >> 1) + 2 + (i & 1)]);
                    mx[i] = fmaxf(mx[i], __shfl_xor_sync(~0u, mx[i], 4));
                    mx[i] = fmaxf(mx[i], __shfl_xor_sync(~0u, mx[i], 8));
                    mx[i] = fmaxf(mx[i], __shfl_xor_sync(~0u, mx[i], 16));
                }
                if (g == 0) {
#pragma unroll
                    for (int jb = 0; jb < 4; jb++)
                        *(float2*)(red + warp * 32 + 8 * jb + 2 * t) = make_float2(mx[2 * jb], mx[2 * jb + 1]);
                }
                named_bar(1, 128);
                float al[8];
                bool chg = false;
                uint32_t R[8];
#pragma unroll
                for (int jb = 0; jb < 4; jb++) {
                    float2 a = *(float2*)(red + 8 * jb + 2 * t), b = *(float2*)(red + 32 + 8 * jb + 2 * t);
                    float2 c = *(float2*)(red + 64 + 8 * jb + 2 * t), d = *(float2*)(red + 96 + 8 * jb + 2 * t);
                    const float n0 = fmaxf(mrun[2 * jb], fmaxf(fmaxf(a.x, b.x), fmaxf(c.x, d.x)) * LOG2E);
                    const float n1 = fmaxf(mrun[2 * jb + 1], fmaxf(fmaxf(a.y, b.y), fmaxf(c.y, d.y)) * LOG2E);
                    chg |= (n0 != mrun[2 * jb]) | (n1 != mrun[2 * jb + 1]);
                    al[2 * jb] = ex2(mrun[2 * jb] - n0);
                    al[2 * jb + 1] = ex2(mrun[2 * jb + 1] - n1);
                    mrun[2 * jb] = n0; mrun[2 * jb + 1] = n1;
                    R[2 * jb]     = pack_bf16(ex2(fmaf(S[4 * jb], LOG2E, -n0)), ex2(fmaf(S[4 * jb + 1], LOG2E, -n1)));
                    R[2 * jb + 1] = pack_bf16(ex2(fmaf(S[4 * jb + 2], LOG2E, -n0)), ex2(fmaf(S[4 * jb + 3], LOG2E, -n1)));
                    lrun[2 * jb]     = fmaf(lrun[2 * jb], al[2 * jb], bf_lo(R[2 * jb]) + bf_lo(R[2 * jb + 1]));
                    lrun[2 * jb + 1] = fmaf(lrun[2 * jb + 1], al[2 * jb + 1], bf_hi(R[2 * jb]) + bf_hi(R[2 * jb + 1]));
                }
                asm volatile("stmatrix.sync.aligned.m8n8.x4.trans.shared.b16 [%0], {%1,%2,%3,%4};"
                             ::"r"(pst), "r"(R[0]), "r"(R[1]), "r"(R[2]), "r"(R[3]) : "memory");
                asm volatile("stmatrix.sync.aligned.m8n8.x4.trans.shared.b16 [%0], {%1,%2,%3,%4};"
                             ::"r"(pst + 2048), "r"(R[4]), "r"(R[5]), "r"(R[6]), "r"(R[7]) : "memory");
                asm volatile("fence.proxy.async.shared::cta;" ::: "memory");
                if (__any_sync(~0u, chg)) {
#pragma unroll
                    for (int mt = 0; mt < 8; mt++)
#pragma unroll
                        for (int k = 0; k < 16; k++) acc[mt][k] *= al[2 * (k >> 2) + (k & 1)];
                }
                named_bar(1, 128);
                wg_fence();
#pragma unroll
                for (int mt = 0; mt < 4; mt++)
#pragma unroll
                    for (int kk = 0; kk < 4; kk++)
                        wgmma_n32<1>(acc[mt], dA0 + (uint64_t)((mt * 8192 + kk * 2048) >> 4), dP + (uint64_t)((kk * 32) >> 4), 1);
                wg_commit();
#pragma unroll
                for (int mt = 0; mt < 4; mt++)
#pragma unroll
                    for (int kk = 0; kk < 4; kk++)
                        wgmma_n32<1>(acc[4 + mt], dA1 + (uint64_t)((mt * 8192 + kk * 2048) >> 4), dP + (uint64_t)((kk * 32) >> 4), 1);
                wg_commit();
                wg_wait<1>();
                if (lane == 0) mbar_arrive(sb + SM_BAR + BAR_BEMPTY + s0 * 8);
                wg_wait<0>();
                if (lane == 0) mbar_arrive(sb + SM_BAR + BAR_BEMPTY + s1 * 8);
                s0 = s1 + 1; ph0 = ph1;
                if (s0 == 5) { s0 = 0; ph0 ^= 1; }
            }
#pragma unroll
            for (int i = 0; i < 8; i++) {
                lrun[i] += __shfl_xor_sync(~0u, lrun[i], 4);
                lrun[i] += __shfl_xor_sync(~0u, lrun[i], 8);
                lrun[i] += __shfl_xor_sync(~0u, lrun[i], 16);
            }
            if (g == 0) {
#pragma unroll
                for (int jb = 0; jb < 4; jb++) {
                    *(float2*)(red + 128 + warp * 32 + 8 * jb + 2 * t) = make_float2(lrun[2 * jb], lrun[2 * jb + 1]);
                    if (warp == 0) *(float2*)(red + 256 + 8 * jb + 2 * t) = make_float2(mrun[2 * jb], mrun[2 * jb + 1]);
                }
            }
            named_bar(1, 128);
            if (tid == 0) mbar_arrive(sb + SM_BAR + BAR_BDONE);
            if (tid < 32)
                G.bml[ib * 32 + tid] = make_float2(red[256 + tid], red[128 + tid] + red[160 + tid] + red[192 + tid] + red[224 + tid]);
            float* bp = G.bpart + (size_t)ib * 16384 + (2 * t) * 512 + 16 * warp + g;
#pragma unroll
            for (int mt = 0; mt < 8; mt++)
#pragma unroll
                for (int k = 0; k < 16; k++)
                    bp[(8 * (k >> 2) + (k & 1)) * 512 + 64 * mt + ((k >> 1) & 1) * 8] = acc[mt][k];
            named_bar(1, 128);
            if (tid == 0) red_release(&G.cntB.v);
            STAMP(tid == 0, 6);
        }

        if (hasSlice) {
            if (tid == 0) {
                wait_prog(smem + SM_BAR + W_PROG, TUV);
                wait_counter(&G.cntB.v, (epoch + 1) * NB_CTA, 500);
                if (cta == 0) st_relaxed32(&G.epoch.v, epoch + 1);
                asm volatile("prefetch.tensormap [%0];" ::"l"(&M.m_uv[late]) : "memory");
                asm volatile("prefetch.tensormap [%0];" ::"l"(&M.m_w[mat]) : "memory");
            }
            named_bar(1, 128);
            if (tid == 32) mbar_arrive(sb + SM_BAR + BAR_PDONE);
            STAMP(tid == 0, 7);
            {
                const int b = tid >> 6, cp = tid & 63;
                uint2 ml[8];
#pragma unroll
                for (int i = 0; i < 8; i++) ml[i] = ld_relaxed64(G.bml + (b * 8 + i) * 32 + h);
                uint4 pv[2][8];
#pragma unroll
                for (int i = 0; i < 16; i++)
                    pv[i >> 3][i & 7] = ld_relaxed128(G.bpart + (size_t)(b * 8 + (i & 7)) * 16384 + h * 512 + (i >> 3) * 256 + 4 * cp);
                float M = __uint_as_float(ml[0].x);
#pragma unroll
                for (int i = 1; i < 8; i++) M = fmaxf(M, __uint_as_float(ml[i].x));
                float L = 0.f, wgt[8];
#pragma unroll
                for (int i = 0; i < 8; i++) {
                    wgt[i] = ex2(__uint_as_float(ml[i].x) - M);
                    L = fmaf(wgt[i], __uint_as_float(ml[i].y), L);
                }
                const float inv = 1.f / L;
#pragma unroll
                for (int x = 0; x < 2; x++) {
                    float v0 = 0.f, v1 = 0.f, v2 = 0.f, v3 = 0.f;
#pragma unroll
                    for (int i = 0; i < 8; i++) {
                        v0 = fmaf(wgt[i], __uint_as_float(pv[x][i].x), v0);
                        v1 = fmaf(wgt[i], __uint_as_float(pv[x][i].y), v1);
                        v2 = fmaf(wgt[i], __uint_as_float(pv[x][i].z), v2);
                        v3 = fmaf(wgt[i], __uint_as_float(pv[x][i].w), v3);
                    }
                    *(uint2*)(smem + SM_P + b * 1024 + x * 512 + cp * 8) = make_uint2(pack_bf16(v0 * inv, v1 * inv), pack_bf16(v2 * inv, v3 * inv));
                }
            }
            STAMP(tid == 0, 8);
        }
        {
            named_bar(1, 128);
#pragma unroll 1
            for (uint64_t plan = j < 64 ? 0xF7351260ull : (j < 124 ? (late ? 0xF75314260ull : 0xF7514603ull) : (hasSlice ? 0xF753426ull : 0xF10ull));
                 plan != 0xF; plan >>= 4) {
                const int step = plan & 15;
                if ((step & 14) == 4) {
                    const int hh = rg + 8 * warp;
                    const uint32_t real = step & 1, both = real & (mat | (warp != 3));
                    if (both) wait_ticket(smem + SM_BAR + W_PROG, mat ? NT + YB : min((33 + hh) * 128 + LAGT, NT + YLATE) + YX);
                    __syncwarp();
                    const float* src = (mat ? G.ctx : G.o) + hh * 128 + lane * 4;
                    uint4 v[2];
                    v[0] = v[1] = make_uint4(tag, tag, tag, tag);
                    uint32_t bad0 = real, bad1 = both;
                    unsigned it = 0;
                    while (true) {
                        ld_relaxed128_if(v[0], src, bad0);
                        ld_relaxed128_if(v[1], src + 4096, bad1);
                        bad0 = bad4(v[0], tag) & 1u; bad1 = bad4(v[1], tag) & 1u;
                        if (!__any_sync(~0u, bad0 | bad1)) break;
                        if (++it > SPIN_LIMIT) __trap();
                    }
#pragma unroll
                    for (int b = 0; b < 2; b++)
                        *(uint2*)(smem + SM_VEC + V_X + b * XSTR + (128 * warp + 4 * lane) * 2) =
                            make_uint2(pack_bf16(__uint_as_float(v[b].x), __uint_as_float(v[b].y)), pack_bf16(__uint_as_float(v[b].z), __uint_as_float(v[b].w)));
                    named_bar(1, 128);
                    STAMP(tid == 0, 29);
                } else if (step >= 6) {
                    const uint32_t real = step & 1;
                    const uint32_t xa = sb + SM_VEC + V_X + ((lane >> 1) & 1) * XSTR + 8 * (lane >> 3) * 2;
                    const uint32_t wa = sb + SM_SQ + 2 * 16384 + (8 * (lane >> 4) + (lane & 7)) * 128 +
                                        (((2 * warp + ((lane >> 3) & 1)) ^ (lane & 7)) << 4);
                    const uint32_t bs = sb + SM_BAR + BAR_S + 16;
                    const float* src = G.o + 4096 + (24 + rg) * 128 + lane * 4;
                    const uint32_t needx = real & (mat ^ 1);
                    uint32_t* dst = (uint32_t*)P.out + (t & 1) * 512 + mat * 256 + cg * 32 + warp * 8 + (t >> 1) * 4 + (g >> 1);
                    asm volatile("" : "+l"(dst));
                    uint4 v = make_uint4(tag, tag, tag, tag);
                    float d[4][4];
#pragma unroll
                    for (int i = 0; i < 16; i++) (&d[0][0])[i] = 0.f;
#pragma unroll 1
                    for (int u = 0; u < 3; u++) {
                        uint4 xf[4];
                        if (needx && u == 2) wait_ticket(smem + SM_BAR + W_PROG, NT + YP);
                        __syncwarp();
                        ld_relaxed128_if(v, src, needx & (u == 2));
#pragma unroll
                        for (int i = 0; i < 4; i++) xf[i] = ldsm4(xa + u * 256 + i * 64);
                        if (real) mbar_wait_nt(bs + u * 8, 0);
#pragma unroll
                        for (int i = 0; i < 4; i++) {
                            const uint4 w0 = ldsm4t(wa + u * 16384 + i * 4096), w1 = ldsm4t(wa + u * 16384 + i * 4096 + 2048);
                            mma16816(d[(i & 1) * 2], w0.x, w0.y, w0.z, w0.w, xf[i].x, xf[i].y);
                            mma16816(d[(i & 1) * 2 + 1], w1.x, w1.y, w1.z, w1.w, xf[i].z, xf[i].w);
                        }
                    }
                    unsigned it = 0;
                    while (__any_sync(~0u, bad4(v, tag) & 1u)) {
                        if (++it > SPIN_LIMIT) __trap();
                        v = ld_relaxed128(src);
                    }
                    STAMP(tid == 96, 20);
                    if (!mat)
                        *(uint2*)(smem + SM_VEC + V_X + XSTR + (384 + 4 * lane) * 2) =
                            make_uint2(pack_bf16(__uint_as_float(v.x), __uint_as_float(v.y)), pack_bf16(__uint_as_float(v.z), __uint_as_float(v.w)));
                    __syncwarp();
                    uint4 xf[4], w[4];
#pragma unroll
                    for (int i = 0; i < 4; i++) xf[i] = ldsm4(xa + 3 * 256 + i * 64);
#pragma unroll
                    for (int q = 0; q < 2; q++) {
                        if (q) {
#pragma unroll
                            for (int i = 0; i < 4; i++) {
                                d[0][i] = (d[0][i] + d[1][i]) + (d[2][i] + d[3][i]);
                                d[1][i] = d[2][i] = d[3][i] = 0.f;
                            }
                        }
                        if (real) mbar_wait_nt(bs + 24 + q * 8, 0);
#pragma unroll
                        for (int i = 0; i < 4; i++) w[i] = ldsm4t(wa + 3 * 16384 + q * 8192 + i * 2048);
#pragma unroll
                        for (int i = 0; i < 2; i++) {
                            mma16816(d[2 * i], w[2 * i].x, w[2 * i].y, w[2 * i].z, w[2 * i].w, xf[2 * q + i].x, xf[2 * q + i].y);
                            mma16816(d[2 * i + 1], w[2 * i + 1].x, w[2 * i + 1].y, w[2 * i + 1].z, w[2 * i + 1].w, xf[2 * q + i].z, xf[2 * q + i].w);
                        }
                    }
                    STAMP(tid == 64, 22);
                    float e[4];
#pragma unroll
                    for (int i = 0; i < 4; i++) e[i] = (t & 2) ? d[i][2] : d[i][0];
                    red_out(dst, ((e[0] + e[1]) + e[2]) + e[3], g, real);
                    STAMP(tid == 64, 13);
                    if (real) asm volatile("exit;");
                } else if (step >= 2) {
                    uint2 bf[16];
                    tall_prep(bf, sb + SM_P, warp, g, t);
                    if (step & 1) mbar_wait(sb + SM_BAR + BAR_S + (warp >> 1) * 8, 0);
                    LAND(tid == 64, 17408 + 3 * 128 + j);
                    gemv_tall(sb + SM_SQ, bf, red + 512, warp, g, t);
                    tall_finish(red + 512, G.ctx + ((tid >> 5) & 1) * 4096 + 32 * j + (tid & 31), tid, tag, 0, (step & 1) ? 64 : 0);
                    STAMP(tid == 0, 12);
                } else {
                    const int b = step;
                    const int hm = min(h, 31), bh = 32 * b + hm;
                    wait_ticket(smem + SM_BAR + W_PROG, min((bh + 1) * 128 + LAGT, NT + YLATE + max(hm - 27, 0) * YSL));
                    __syncwarp();
                    float* rb = red + b * 256;
                    combineA(G, bh, qd, tag, rb, tid, smem + SM_BAR + W_PROG);
                    {
                        if (tid < 32)
                            st_relaxed32(G.o + bh * 128 + 32 * qd + tid, tagw((rb[tid] + rb[32 + tid]) + (rb[64 + tid] + rb[96 + tid]), tag));
                        STAMP(tid == 0, 9 + 2 * b);
                    }
                }
            }
        }
    }
}

typedef CUresult (*EncodeFn)(CUtensorMap*, CUtensorMapDataType, cuuint32_t, void*, const cuuint64_t*, const cuuint64_t*,
                             const cuuint32_t*, const cuuint32_t*, CUtensorMapInterleave, CUtensorMapSwizzle,
                             CUtensorMapL2promotion, CUtensorMapFloatOOBfill);

}

extern "C" void kernel_launch(void* const* d_in, const int* in_sizes, int n_in, void* d_out, int out_size) {
    (void)in_sizes; (void)n_in; (void)out_size;
    static EncodeFn encode = nullptr;
    static void* scratch = nullptr;
    if (!encode) {
        void* fn = nullptr;
        cudaDriverEntryPointQueryResult st;
        cudaGetDriverEntryPoint("cuTensorMapEncodeTiled", &fn, cudaEnableDefault, &st);
        encode = (EncodeFn)fn;
        cudaGetSymbolAddress(&scratch, g_raw);
        cudaFuncSetAttribute(fused_decode_kernel, cudaFuncAttributeMaxDynamicSharedMemorySize, SM_TOTAL);
    }
    Ptrs P;
    Maps M;
    auto mk = [&](CUtensorMap* m, void* ptr, cuuint64_t cols, cuuint64_t rows, cuuint32_t bc, cuuint32_t br, CUtensorMapSwizzle sw,
                  CUtensorMapL2promotion promo) {
        const cuuint64_t gdim[2] = {cols, rows};
        const cuuint64_t gstr[1] = {cols * 2};
        const cuuint32_t box[2] = {bc, br};
        const cuuint32_t estr[2] = {1, 1};
        encode(m, CU_TENSOR_MAP_DATA_TYPE_BFLOAT16, 2, ptr, gdim, gstr, box, estr, CU_TENSOR_MAP_INTERLEAVE_NONE, sw,
               promo, CU_TENSOR_MAP_FLOAT_OOB_FILL_NONE);
    };
    mk(&M.m_wq, d_in[3], 4096, 512, 32, 256, CU_TENSOR_MAP_SWIZZLE_64B, CU_TENSOR_MAP_L2_PROMOTION_NONE);
    auto mk3 = [&](CUtensorMap* m, void* ptr, cuuint64_t cols, cuuint64_t rows) {
        const cuuint64_t gdim[3] = {64, rows, cols / 64};
        const cuuint64_t gstr[2] = {cols * 2, 128};
        const cuuint32_t box[3] = {64, 64, 2};
        const cuuint32_t estr[3] = {1, 1, 1};
        encode(m, CU_TENSOR_MAP_DATA_TYPE_BFLOAT16, 3, ptr, gdim, gstr, box, estr, CU_TENSOR_MAP_INTERLEAVE_NONE,
               CU_TENSOR_MAP_SWIZZLE_128B, CU_TENSOR_MAP_L2_PROMOTION_L2_256B, CU_TENSOR_MAP_FLOAT_OOB_FILL_NONE);
    };
    mk3(&M.m_v, d_in[2], 128, 524288);
    mk(&M.m_uv[0], d_in[9], 4096, 512, 32, 128, CU_TENSOR_MAP_SWIZZLE_64B, CU_TENSOR_MAP_L2_PROMOTION_NONE);
    mk(&M.m_uv[1], d_in[9], 4096, 512, 32, 128, CU_TENSOR_MAP_SWIZZLE_64B, CU_TENSOR_MAP_L2_PROMOTION_L2_256B);
    mk(&M.m_w[0], d_in[4], 512, 4096, 64, 64, CU_TENSOR_MAP_SWIZZLE_128B, CU_TENSOR_MAP_L2_PROMOTION_L2_256B);
    mk(&M.m_w[1], d_in[10], 512, 4096, 64, 64, CU_TENSOR_MAP_SWIZZLE_128B, CU_TENSOR_MAP_L2_PROMOTION_L2_256B);
    mk(&M.m_ckv, d_in[6], 512, 16384, 64, 64, CU_TENSOR_MAP_SWIZZLE_128B, CU_TENSOR_MAP_L2_PROMOTION_L2_256B);
    mk(&M.m_wqB, d_in[7], 4096, 512, 32, 256, CU_TENSOR_MAP_SWIZZLE_64B, CU_TENSOR_MAP_L2_PROMOTION_NONE);
    mk(&M.m_wuk, d_in[8], 4096, 512, 128, 128, CU_TENSOR_MAP_SWIZZLE_NONE, CU_TENSOR_MAP_L2_PROMOTION_L2_256B);
    P.xA = (const __nv_bfloat16*)d_in[0];
    P.K = (const __nv_bfloat16*)d_in[1];
    P.xB = (const __nv_bfloat16*)d_in[5];
    P.out = (__nv_bfloat16*)d_out;
    P.g = (Scratch*)scratch;
    cudaLaunchConfig_t cfg = {};
    cfg.gridDim = dim3(GRID);
    cfg.blockDim = dim3(NTHREADS);
    cfg.dynamicSmemBytes = SM_TOTAL;
    cfg.stream = cudaStreamPerThread;
    cudaLaunchAttribute attr;
    attr.id = cudaLaunchAttributeCooperative;
    attr.val.cooperative = 1;
    cfg.attrs = &attr;
    cfg.numAttrs = 1;
    cudaLaunchKernelEx(&cfg, fused_decode_kernel, P, M);
}
```

```cpp
#include <cuda_runtime.h>
#include <cuda_bf16.h>
#include <cuda.h>
#include <stdint.h>

namespace {

constexpr int NT       = 8192;
constexpr int GRID     = 132;
constexpr int NB_CTA   = 16;
constexpr int NA_CTA   = GRID - NB_CTA;
constexpr int NWORK    = 3;
#define YV 292
#define DV 56
#define YW 407
#define DW 68
#define DL 6
#define YX 150
#define YB 582
#define YP 605
#define XRV 330
#define TV 3200
#define PFB 8192
#define LAGT 1060
#define YLATE 120
#define YSL 70
#define YO 450
#define YOS 40
#define TUV (43 * 128)
#define XPK 80
#define FRZ 60
#define QDELAY 500
constexpr int NEARX = 400;
constexpr int JE0   = 112;
constexpr int HCLR  = 26;
constexpr int BINFL = 2;
constexpr int NSTATIC  = NA_CTA * NWORK;
constexpr unsigned DRAWS = (NT - NSTATIC) + GRID * NWORK;
static_assert(52 * 128 + LAGT + 300 <= NT && TUV + 10 * 128 <= NT, "wait_prog thresholds must be reachable");
constexpr int NTHREADS = 256;
constexpr float SCALE = 0.08838834764831845f, LOG2E = 1.4426950408889634f;
constexpr unsigned SPIN_LIMIT = 1u << 22;

constexpr int SM_SLOT  = 0;
constexpr int SM_QA    = 196608;
constexpr int SM_P     = SM_QA + 16384;
constexpr int SM_RED1  = SM_P + 4096;
constexpr int SM_RED2  = SM_RED1 + 2048;
constexpr int SM_VEC   = SM_RED2 + 4096;
constexpr int SM_BAR   = SM_VEC + 3072;
constexpr int SM_TOTAL = SM_BAR + 352;
constexpr int V_X    = 512;
constexpr int BAR_FULL = 0;
constexpr int BAR_PDONE= 48;
constexpr int BAR_BDONE= 56;
constexpr int BAR_QABS = 72;
constexpr int BAR_BFULL= 80;
constexpr int BAR_BEMPTY=120;
constexpr int BAR_WFREE= 160;
constexpr int BAR_W    = 168;
constexpr int BAR_S    = 192;
constexpr int BAR_Q    = 264;
constexpr int W_EPOCH  = 328;
constexpr int W_PROG   = 336;
constexpr int SM_WQ = 3 * 32768, SM_WQB = 4 * 32768, SM_WUK = 5 * 32768;
constexpr int SM_SQ = 3 * 32768;
constexpr int XSTR = 1024 + 16;

struct __align__(128) Cnt { unsigned v; unsigned pad[31]; };
struct __align__(128) Scratch {
    Cnt epoch, ticket, cntQabs, cntB;
    float qA[64 * 128], qB[64 * 128];
    __nv_bfloat16 qabs[2 * 32 * 512];
    float  partO[NT * 128];
    float2 partML[NT * 4];
    float  bpart[NB_CTA * 32 * 512];
    float2 bml[NB_CTA * 32];
    float  ctx[32 * 4 * 2 * 128];
    float  o[2 * 4096];
};
__device__ __align__(128) unsigned char g_raw[sizeof(Scratch)];

__device__ __forceinline__ int slice_of(int cta) {
    return cta >= 128 ? cta : ((cta & 8) << 3) | ((cta >> 4) << 3) | (cta & 7);
}

#define STAMP(cond, i) do {} while (0)
#define LAND(cond, i) do {} while (0)

__device__ __forceinline__ void mbar_init(uint32_t bar, int cnt) {
    asm volatile("mbarrier.init.shared::cta.b64 [%0], %1;" ::"r"(bar), "r"(cnt) : "memory");
}
__device__ __forceinline__ void mbar_expect_tx(uint32_t bar, uint32_t bytes) {
    asm volatile("mbarrier.arrive.expect_tx.shared::cta.b64 _, [%0], %1;" ::"r"(bar), "r"(bytes) : "memory");
}
__device__ __forceinline__ void mbar_arrive(uint32_t bar) {
    asm volatile("mbarrier.arrive.shared::cta.b64 _, [%0];" ::"r"(bar) : "memory");
}
__device__ __forceinline__ void mbar_wait(uint32_t bar, uint32_t parity) {
    unsigned it = 0;
    while (true) {
        uint32_t ok;
        asm volatile("{\n.reg .pred p;\nmbarrier.try_wait.parity.shared::cta.b64 p, [%1], %2;\nselp.u32 %0, 1, 0, p;\n}\n"
                     : "=r"(ok) : "r"(bar), "r"(parity) : "memory");
        if (ok) break;
        if (++it > SPIN_LIMIT) __trap();
    }
}
__device__ __forceinline__ void mbar_wait_nt(uint32_t bar, uint32_t parity) {
#pragma unroll 1
    for (unsigned it = 0; it < SPIN_LIMIT; it++) {
        uint32_t ok;
        asm volatile("{\n.reg .pred p;\nmbarrier.try_wait.parity.shared::cta.b64 p, [%1], %2;\nselp.u32 %0, 1, 0, p;\n}\n"
                     : "=r"(ok) : "r"(bar), "r"(parity) : "memory");
        if (ok) break;
    }
}
__device__ __forceinline__ bool mbar_test(uint32_t bar, uint32_t parity) {
    uint32_t ok;
    asm volatile("{\n.reg .pred p;\nmbarrier.test_wait.parity.shared::cta.b64 p, [%1], %2;\nselp.u32 %0, 1, 0, p;\n}\n"
                 : "=r"(ok) : "r"(bar), "r"(parity) : "memory");
    return ok;
}
__device__ __forceinline__ void bulk_load(uint32_t dst, const void* src, uint32_t bytes, uint32_t bar, uint64_t pol) {
    asm volatile("cp.async.bulk.shared::cluster.global.mbarrier::complete_tx::bytes.L2::cache_hint [%0], [%1], %2, [%3], %4;"
                 ::"r"(dst), "l"(src), "r"(bytes), "r"(bar), "l"(pol) : "memory");
}
__device__ __forceinline__ void bulk_load_nohint(uint32_t dst, const void* src, uint32_t bytes, uint32_t bar) {
    asm volatile("cp.async.bulk.shared::cluster.global.mbarrier::complete_tx::bytes [%0], [%1], %2, [%3];"
                 ::"r"(dst), "l"(src), "r"(bytes), "r"(bar) : "memory");
}
__device__ __forceinline__ void tma_2d(uint32_t dst, const CUtensorMap* map, int c0, int c1, uint32_t bar, uint64_t pol) {
    asm volatile("cp.async.bulk.tensor.2d.shared::cluster.global.mbarrier::complete_tx::bytes.L2::cache_hint [%0], [%1, {%3, %4}], [%2], %5;"
                 ::"r"(dst), "l"(map), "r"(bar), "r"(c0), "r"(c1), "l"(pol) : "memory");
}
__device__ __forceinline__ void tma_3d(uint32_t dst, const CUtensorMap* map, int c1, int c2, uint32_t bar, uint64_t pol) {
    asm volatile("cp.async.bulk.tensor.3d.shared::cluster.global.mbarrier::complete_tx::bytes.L2::cache_hint [%0], [%1, {%3, %4, %5}], [%2], %6;"
                 ::"r"(dst), "l"(map), "r"(bar), "r"(0), "r"(c1), "r"(c2), "l"(pol) : "memory");
}
__device__ __forceinline__ void wait_prog(const unsigned char* smem_word, unsigned th) {
    unsigned it = 0;
    while (*(volatile const unsigned*)(smem_word + 8) + NSTATIC < th) {
        __nanosleep(60);
        if (++it > SPIN_LIMIT) __trap();
    }
}
__device__ __forceinline__ uint32_t now_ns() {
    uint32_t t;
    asm volatile("mov.u32 %0, %globaltimer_lo;" : "=r"(t) :: "memory");
    return t;
}
__device__ __forceinline__ void note_draw(unsigned char* smem_word, unsigned raw) {
    const uint32_t a = (uint32_t)__cvta_generic_to_shared(smem_word);
    asm volatile("st.volatile.u32 [%0], %1;" ::"l"(smem_word + 8), "r"(raw) : "memory");
    const uint32_t now = now_ns();
    if ((int)raw < NT - NSTATIC - FRZ) asm volatile("st.volatile.shared.v2.u32 [%0], {%1, %2};" ::"r"(a), "r"(raw), "r"(now) : "memory");
}
__device__ __forceinline__ void wait_ticket(const unsigned char* smem_word, int th) {
    wait_prog(smem_word, min(th, NT - NEARX));
    uint32_t tk, t0;
#pragma unroll 1
    for (unsigned it = 0; it < SPIN_LIMIT; it++) {
        asm volatile("ld.volatile.shared.v2.u32 {%0, %1}, [%2];" : "=r"(tk), "=r"(t0) : "r"((uint32_t)__cvta_generic_to_shared(smem_word)) : "memory");
        if ((int)(now_ns() - t0) >= (th - NSTATIC - (int)tk) * 10) break;
        __nanosleep(20);
    }
}
__device__ __forceinline__ bool mbar_wait_for(uint32_t bar, uint32_t parity, int n) {
    uint32_t c0, c;
    asm volatile("mov.u32 %0, %%clock;" : "=r"(c0) :: "memory");
    do {
        if (mbar_test(bar, parity)) return true;
        asm volatile("mov.u32 %0, %%clock;" : "=r"(c) :: "memory");
    } while ((int)(c - c0) < n);
    return false;
}
__device__ __forceinline__ bool elect_one() {
    uint32_t p;
    asm volatile("{\n.reg .pred p;\nelect.sync _|p, 0xffffffff;\nselp.u32 %0, 1, 0, p;\n}\n" : "=r"(p));
    return p;
}
__device__ __forceinline__ void fence_proxy_async() { asm volatile("fence.proxy.async;" ::: "memory"); }
__device__ __forceinline__ void named_bar(int id, int n) { asm volatile("bar.sync %0, %1;" ::"r"(id), "r"(n) : "memory"); }

__device__ __forceinline__ uint4 lds128(uint32_t a) {
    uint4 v;
    asm volatile("ld.shared.v4.u32 {%0,%1,%2,%3}, [%4];" : "=r"(v.x), "=r"(v.y), "=r"(v.z), "=r"(v.w) : "r"(a));
    return v;
}
__device__ __forceinline__ uint4 ldsm4(uint32_t a) {
    uint4 v;
    asm volatile("ldmatrix.sync.aligned.m8n8.x4.shared.b16 {%0,%1,%2,%3}, [%4];" : "=r"(v.x), "=r"(v.y), "=r"(v.z), "=r"(v.w) : "r"(a));
    return v;
}
__device__ __forceinline__ uint4 ldsm4t(uint32_t a) {
    uint4 v;
    asm volatile("ldmatrix.sync.aligned.m8n8.x4.trans.shared.b16 {%0,%1,%2,%3}, [%4];" : "=r"(v.x), "=r"(v.y), "=r"(v.z), "=r"(v.w) : "r"(a));
    return v;
}
__device__ __forceinline__ uint2 lds64(uint32_t a) {
    uint2 v;
    asm volatile("ld.shared.v2.u32 {%0,%1}, [%2];" : "=r"(v.x), "=r"(v.y) : "r"(a));
    return v;
}
__device__ __forceinline__ uint4 ld_relaxed128(const void* p) {
    uint4 v;
    asm volatile("ld.relaxed.gpu.global.v4.u32 {%0,%1,%2,%3}, [%4];" : "=r"(v.x), "=r"(v.y), "=r"(v.z), "=r"(v.w) : "l"(p) : "memory");
    return v;
}
__device__ __forceinline__ uint2 ld_relaxed64(const void* p) {
    uint2 v;
    asm volatile("ld.relaxed.gpu.global.v2.u32 {%0,%1}, [%2];" : "=r"(v.x), "=r"(v.y) : "l"(p) : "memory");
    return v;
}
__device__ __forceinline__ uint32_t ld_relaxed32(const void* p) {
    uint32_t v;
    asm volatile("ld.relaxed.gpu.global.u32 %0, [%1];" : "=r"(v) : "l"(p) : "memory");
    return v;
}
__device__ __forceinline__ uint32_t ld_acquire32(const void* p) {
    uint32_t v;
    asm volatile("ld.acquire.gpu.global.u32 %0, [%1];" : "=r"(v) : "l"(p) : "memory");
    return v;
}
__device__ __forceinline__ void st_relaxed128(void* p, uint32_t a, uint32_t b, uint32_t c, uint32_t d) {
    asm volatile("st.relaxed.gpu.global.v4.u32 [%0], {%1,%2,%3,%4};" ::"l"(p), "r"(a), "r"(b), "r"(c), "r"(d) : "memory");
}
__device__ __forceinline__ void red_release(unsigned* p) {
    asm volatile("red.release.gpu.global.add.u32 [%0], 1;" ::"l"(p) : "memory");
}
__device__ __forceinline__ void wait_counter(const unsigned* p, unsigned target, unsigned ns) {
    unsigned it = 0;
    while ((int)(ld_acquire32(p) - target) < 0) {
        __nanosleep(ns);
        if (++it > SPIN_LIMIT) __trap();
    }
}
__device__ __forceinline__ uint32_t prmt(uint32_t a, uint32_t b, uint32_t s) {
    uint32_t d;
    asm("prmt.b32 %0, %1, %2, %3;" : "=r"(d) : "r"(a), "r"(b), "r"(s));
    return d;
}
__device__ __forceinline__ uint32_t pack_bf16(float lo, float hi) {
    uint32_t d;
    asm("cvt.rn.bf16x2.f32 %0, %1, %2;" : "=r"(d) : "f"(hi), "f"(lo));
    return d;
}
__device__ __forceinline__ float ex2(float x) {
    float y;
    asm("ex2.approx.ftz.f32 %0, %1;" : "=f"(y) : "f"(x));
    return y;
}
__device__ __forceinline__ float bf_lo(uint32_t v) { return __uint_as_float(v << 16); }
__device__ __forceinline__ float bf_hi(uint32_t v) { return __uint_as_float(v & 0xffff0000u); }
__device__ __forceinline__ void scale_scores(float& a, float& b) {
    uint32_t p = pack_bf16(a, b);
    p = pack_bf16(bf_lo(p) * SCALE, bf_hi(p) * SCALE);
    a = bf_lo(p); b = bf_hi(p);
}
__device__ __forceinline__ uint32_t tagw(float v, uint32_t tag) {
    uint32_t d;
    asm("lop3.b32 %0, %1, 0xfffffffe, %2, 0xEA;" : "=r"(d) : "r"(__float_as_uint(v)), "r"(tag));
    return d;
}
__device__ __forceinline__ uint32_t bad2(uint32_t x, uint32_t y, uint32_t tag) {
    uint32_t d;
    asm("lop3.b32 %0, %1, %2, %3, 0x7E;" : "=r"(d) : "r"(x), "r"(y), "r"(tag));
    return d;
}
__device__ __forceinline__ uint32_t bad4(const uint4& v, uint32_t tag) { return bad2(v.x, v.y, tag) | bad2(v.z, v.w, tag); }
__device__ __forceinline__ void ld_relaxed128_if(uint4& v, const void* p, uint32_t c) {
    asm volatile("{\n.reg .pred p;\nsetp.ne.u32 p, %5, 0;\n@p ld.relaxed.gpu.global.v4.u32 {%0,%1,%2,%3}, [%4];\n}\n"
                 : "+r"(v.x), "+r"(v.y), "+r"(v.z), "+r"(v.w) : "l"(p), "r"(c) : "memory");
}
__device__ __forceinline__ void ld_relaxed64_if(uint2& v, const void* p, uint32_t c) {
    asm volatile("{\n.reg .pred p;\nsetp.ne.u32 p, %3, 0;\n@p ld.relaxed.gpu.global.v2.u32 {%0,%1}, [%2];\n}\n"
                 : "+r"(v.x), "+r"(v.y) : "l"(p), "r"(c) : "memory");
}
__device__ __forceinline__ void st_relaxed32(void* p, uint32_t a) {
    asm volatile("st.relaxed.gpu.global.u32 [%0], %1;" ::"l"(p), "r"(a) : "memory");
}
__device__ __forceinline__ void red_out(uint32_t* word, float v, int col, uint32_t go) {
    const uint32_t pk = (col & 1) ? pack_bf16(-0.f, v) : pack_bf16(v, -0.f);
    asm volatile("{\n.reg .pred p;\nsetp.ne.u32 p, %2, 0;\n@p red.relaxed.gpu.global.add.noftz.bf16x2 [%0], %1;\n}\n"
                 ::"l"(word), "r"(pk), "r"(go) : "memory");
}
__device__ __forceinline__ void mma16816(float (&c)[4], uint32_t a0, uint32_t a1, uint32_t a2, uint32_t a3,
                                         uint32_t b0, uint32_t b1) {
    asm("mma.sync.aligned.m16n8k16.row.col.f32.bf16.bf16.f32 {%0,%1,%2,%3}, {%4,%5,%6,%7}, {%8,%9}, {%0,%1,%2,%3};"
        : "+f"(c[0]), "+f"(c[1]), "+f"(c[2]), "+f"(c[3])
        : "r"(a0), "r"(a1), "r"(a2), "r"(a3), "r"(b0), "r"(b1));
}
__device__ __forceinline__ uint64_t make_desc(uint32_t addr) {
    return (uint64_t)((addr & 0x3FFFF) >> 4) | ((uint64_t)1 << 16) | ((uint64_t)64 << 32) | ((uint64_t)1 << 62);
}
template <int TRANS_A>
__device__ __forceinline__ void wgmma_n32(float (&d)[16], uint64_t da, uint64_t db, int scale_d) {
    asm volatile("{\n.reg .pred p;\nsetp.ne.b32 p, %18, 0;\n"
                 "wgmma.mma_async.sync.aligned.m64n32k16.f32.bf16.bf16 "
                 "{%0,%1,%2,%3,%4,%5,%6,%7,%8,%9,%10,%11,%12,%13,%14,%15}, %16, %17, p, 1, 1, %19, 0;\n}\n"
                 : "+f"(d[0]), "+f"(d[1]), "+f"(d[2]), "+f"(d[3]), "+f"(d[4]), "+f"(d[5]), "+f"(d[6]), "+f"(d[7]),
                   "+f"(d[8]), "+f"(d[9]), "+f"(d[10]), "+f"(d[11]), "+f"(d[12]), "+f"(d[13]), "+f"(d[14]), "+f"(d[15])
                 : "l"(da), "l"(db), "r"(scale_d), "n"(TRANS_A));
}
__device__ __forceinline__ void wg_fence()  { asm volatile("wgmma.fence.sync.aligned;" ::: "memory"); }
__device__ __forceinline__ void wg_commit() { asm volatile("wgmma.commit_group.sync.aligned;" ::: "memory"); }
template <int N> __device__ __forceinline__ void wg_wait() { asm volatile("wgmma.wait_group.sync.aligned %0;" ::"n"(N) : "memory"); }

__device__ __forceinline__ void issue_tall(uint32_t dst, const CUtensorMap* map, int col, int row, uint32_t bar, uint64_t pol) {
    tma_2d(dst, map, col, row, bar, pol);
    tma_2d(dst + 16384, map, col, row + 256, bar, pol);
}
__device__ __forceinline__ void tall_prep(uint2 (&bf)[16], uint32_t xbase, int w4, int g, int t) {
    const uint32_t xp = xbase + ((g >> 1) & 1) * 1024 + w4 * 256 + (t >> 1) * 8;
    const uint32_t sel = (g & 1) ? ((t & 1) ? 0x3244u : 0x1044u) : ((t & 1) ? 0x4432u : 0x4410u);
#pragma unroll
    for (int i = 0; i < 16; i++) {
        const uint2 xw = lds64(xp + i * 16);
        bf[i] = make_uint2(prmt(xw.x, 0, sel), prmt(xw.y, 0, sel));
    }
}
__device__ __forceinline__ void gemv_tall(uint32_t wbase, const uint2 (&bf)[16], float* red, int w4, int g, int t) {
    const uint32_t wu = wbase + (128 * w4 + (t & 1) + 4 * (t >> 1)) * 64 + (((g >> 1) ^ (t & 2)) << 4) + (g & 1) * 8;
    const uint32_t wv = (wu + 128) ^ 16;
    float a[4][4];
#pragma unroll
    for (int i = 0; i < 16; i++) (&a[0][0])[i] = 0.f;
#pragma unroll
    for (int i = 0; i < 16; i++) {
        const uint2 u = lds64(wu + i * 512), v = lds64(wv + i * 512);
        mma16816(a[i & 3], u.x, u.y, v.x, v.y, bf[i].x, bf[i].y);
    }
    if (t < 2)
        *(float4*)(red + (w4 * 2 + t) * 32 + 4 * g) =
            make_float4((a[0][0] + a[1][0]) + (a[2][0] + a[3][0]), (a[0][1] + a[1][1]) + (a[2][1] + a[3][1]),
                        (a[0][2] + a[1][2]) + (a[2][2] + a[3][2]), (a[0][3] + a[1][3]) + (a[2][3] + a[3][3]));
}
__device__ __forceinline__ void tall_finish(const float* red, float* dst, int tid, uint32_t tag, int lo = 0, int hi = 64) {
    named_bar(1, 128);
    if (tid >= lo && tid < hi) {
        st_relaxed32(dst, tagw((red[tid] + red[64 + tid]) + (red[128 + tid] + red[192 + tid]), tag));
    }
}

__device__ __forceinline__ void combineA(Scratch& G, int bh, int dq, uint32_t tag, float* red, int tid, const unsigned char* prog) {
    const int r = tid >> 3, c4 = tid & 7, w4 = tid >> 5, lane = tid & 31;
    const float2* ml = G.partML + (bh * 128 + r) * 4;
    const float* po = G.partO + (size_t)(bh * 128 + r) * 128 + dq * 32 + c4 * 4;
    uint2 m[8];
    uint4 o[8];
    uint32_t bad[8];
    STAMP(tid == 0 && bh >= 32, 28);
#pragma unroll
    for (int k = 0; k < 8; k++) m[k] = ld_relaxed64(ml + 64 * k);
#pragma unroll
    for (int k = 0; k < 8; k++) {
        o[k] = make_uint4(~tag, ~tag, ~tag, ~tag);
        ld_relaxed128_if(o[k], po + (size_t)k * 16 * 128, bh < 60);
    }
    unsigned it = 0;
    while (true) {
        uint32_t any = 0;
#pragma unroll
        for (int k = 0; k < 8; k++) { bad[k] = bad2(m[k].x, m[k].y, tag) & 1u; any |= bad[k]; }
        if (!__any_sync(~0u, any)) break;
#pragma unroll
        for (int k = 0; k < 8; k++) ld_relaxed64_if(m[k], ml + 64 * k, bad[k]);
        if (++it > SPIN_LIMIT) __trap();
    }
    STAMP(tid == 0 && bh >= 32, 30);
    STAMP(tid == 0 && bh >= 32, 19);
    float M = fmaxf(fmaxf(fmaxf(__uint_as_float(m[0].x), __uint_as_float(m[1].x)), fmaxf(__uint_as_float(m[2].x), __uint_as_float(m[3].x))),
                    fmaxf(fmaxf(__uint_as_float(m[4].x), __uint_as_float(m[5].x)), fmaxf(__uint_as_float(m[6].x), __uint_as_float(m[7].x))));
    M = fmaxf(M, __shfl_xor_sync(~0u, M, 8));
    M = fmaxf(M, __shfl_xor_sync(~0u, M, 16));
    float wgt[8], L = 0.f;
#pragma unroll
    for (int k = 0; k < 8; k++) {
        wgt[k] = ex2(__uint_as_float(m[k].x) - M);
        L = fmaf(wgt[k], __uint_as_float(m[k].y), L);
    }
    L += __shfl_xor_sync(~0u, L, 8);
    L += __shfl_xor_sync(~0u, L, 16);
    if (lane == 0) { red[128 + w4] = M; red[132 + w4] = L; }
    named_bar(1, 128);
    {
        const float4 Mw = *(float4*)(red + 128), Lw = *(float4*)(red + 132);
        const float Mx = fmaxf(fmaxf(Mw.x, Mw.y), fmaxf(Mw.z, Mw.w));
        const float Lt = (ex2(Mw.x - Mx) * Lw.x + ex2(Mw.y - Mx) * Lw.y) + (ex2(Mw.z - Mx) * Lw.z + ex2(Mw.w - Mx) * Lw.w);
        const float f = ex2(M - Mx) / Lt;
#pragma unroll
        for (int k = 0; k < 8; k++) wgt[k] *= f;
    }
    STAMP(tid == 0 && bh >= 32, 23);
    if (bh >= 60) wait_ticket(prog, NT + YO + (bh - 63) * YOS);
    while (true) {
        uint32_t any = 0;
#pragma unroll
        for (int k = 0; k < 8; k++) { bad[k] = bad4(o[k], tag) & 1u; any |= bad[k]; }
        if (!__any_sync(~0u, any)) break;
#pragma unroll
        for (int k = 0; k < 8; k++) ld_relaxed128_if(o[k], po + (size_t)k * 16 * 128, bad[k]);
        if (++it > SPIN_LIMIT) __trap();
    }
    STAMP(tid == 0 && bh >= 32, 31);
    float a0 = 0.f, a1 = 0.f, a2 = 0.f, a3 = 0.f, b0 = 0.f, b1 = 0.f, b2 = 0.f, b3 = 0.f;
#pragma unroll
    for (int k = 0; k < 8; k += 2) {
        a0 = fmaf(wgt[k], __uint_as_float(o[k].x), a0); b0 = fmaf(wgt[k + 1], __uint_as_float(o[k + 1].x), b0);
        a1 = fmaf(wgt[k], __uint_as_float(o[k].y), a1); b1 = fmaf(wgt[k + 1], __uint_as_float(o[k + 1].y), b1);
        a2 = fmaf(wgt[k], __uint_as_float(o[k].z), a2); b2 = fmaf(wgt[k + 1], __uint_as_float(o[k + 1].z), b2);
        a3 = fmaf(wgt[k], __uint_as_float(o[k].w), a3); b3 = fmaf(wgt[k + 1], __uint_as_float(o[k + 1].w), b3);
    }
    a0 += b0; a1 += b1; a2 += b2; a3 += b3;
#pragma unroll
    for (int s = 8; s <= 16; s <<= 1) {
        a0 += __shfl_xor_sync(~0u, a0, s);
        a1 += __shfl_xor_sync(~0u, a1, s);
        a2 += __shfl_xor_sync(~0u, a2, s);
        a3 += __shfl_xor_sync(~0u, a3, s);
    }
    if (lane < 8) *(float4*)(red + w4 * 32 + c4 * 4) = make_float4(a0, a1, a2, a3);
    named_bar(1, 128);
    STAMP(tid == 0 && bh >= 32, 24);
}

struct Ptrs {
    const __nv_bfloat16 *K, *xA, *xB;
    __nv_bfloat16* out;
    Scratch* g;
};
struct Maps { CUtensorMap m_wq, m_v, m_ckv, m_wqB, m_wuk, m_uv[2], m_w[2]; };

__global__ void __launch_bounds__(NTHREADS, 1)
fused_decode_kernel(const Ptrs P, const __grid_constant__ Maps M) {
    extern __shared__ __align__(1024) unsigned char smem[];
    const uint32_t sb = (uint32_t)__cvta_generic_to_shared(smem);
    uint64_t pol;
    asm("createpolicy.fractional.L2::evict_first.b64 %0, 1.0;" : "=l"(pol));
    asm volatile("{\n.reg .pred p;\nsetp.lt.u32 p, %3, 32;\n@p cp.async.bulk.prefetch.L2.global.L2::cache_hint [%0], %1, %2;\n}\n"
                 ::"l"((const char*)P.K + (blockIdx.x << 14)), "n"(PFB), "l"(pol), "r"(threadIdx.x) : "memory");
    if (threadIdx.x < 32 && elect_one()) {
        mbar_init(sb + SM_BAR + BAR_FULL, 1);
        mbar_init(sb + SM_BAR + BAR_W, 1);
        asm volatile("fence.mbarrier_init.release.cluster;" ::: "memory");
        if (blockIdx.x < NA_CTA) {
            mbar_expect_tx(sb + SM_BAR + BAR_FULL, 16384);
            bulk_load(sb + SM_SLOT, (const char*)P.K + (blockIdx.x << 14), 16384, sb + SM_BAR + BAR_FULL, pol);
        }
        if (blockIdx.x < 128) {
            mbar_expect_tx(sb + SM_BAR + BAR_W, 32768 + 4096);
            issue_tall(sb + SM_WQ, &M.m_wq, slice_of(blockIdx.x) * 32, 0, sb + SM_BAR + BAR_W, pol);
            bulk_load_nohint(sb + SM_P, P.xA, 2048, sb + SM_BAR + BAR_W);
            bulk_load_nohint(sb + SM_P + 2048, P.xB, 2048, sb + SM_BAR + BAR_W);
        }
    }
    const int tid = threadIdx.x, warp = __shfl_sync(~0u, tid >> 5, 0), lane = tid & 31;
    const int g = lane >> 2, t = lane & 3;
    const int cta = blockIdx.x;
    Scratch& G = *P.g;
    const bool isB = cta >= NA_CTA;
    const bool hasSlice = cta < 128;
    const int j = slice_of(cta), h = j >> 2, qd = cta & 3;
    const int mat = j >> 6, cg = j & 7, rg = (j >> 3) & 7;
    const bool late = j < JE0 || j >= 124;
    STAMP(tid == 32, 0);
    if (warp == 7) {
        __syncthreads();
        const uint32_t epoch = *(volatile uint32_t*)(smem + SM_BAR + W_EPOCH);
        const uint32_t tag = (epoch + 1) & 1;
        if (!isB) { mbar_wait(sb + SM_BAR + BAR_W, 0); __nanosleep(QDELAY); }
#pragma unroll 1
        for (int i = 0; i < 8; i++) {
            if (i == 4 && !isB) wait_prog(smem + SM_BAR + W_PROG, 16 * 128);
            if (i == 0 && isB) { mbar_wait(sb + SM_BAR + BAR_QABS, 0); __nanosleep(8000); }
            uint4 v[8];
            uint32_t bad[8];
#pragma unroll
            for (int k = 0; k < 8; k++) { bad[k] = 1; v[k] = make_uint4(0, 0, 0, 0); }
            unsigned it = 0;
            while (true) {
#pragma unroll
                for (int k = 0; k < 8; k++) ld_relaxed128_if(v[k], G.qA + (8 * i + k) * 128 + lane * 4, bad[k]);
                uint32_t any = 0;
#pragma unroll
                for (int k = 0; k < 8; k++) { bad[k] = bad4(v[k], tag) & 1u; any |= bad[k]; }
                if (!__any_sync(~0u, any)) break;
                __nanosleep(40);
                if (++it > SPIN_LIMIT) __trap();
            }
#pragma unroll
            for (int k = 0; k < 8; k++) {
                uint32_t* dst = (uint32_t*)(smem + SM_QA + (8 * i + k) * 256 + (lane >> 1) * 16 + (lane & 1) * 4);
                dst[0] = pack_bf16(__uint_as_float(v[k].x), __uint_as_float(v[k].y));
                dst[2] = pack_bf16(__uint_as_float(v[k].z), __uint_as_float(v[k].w));
            }
            __syncwarp();
            if (lane == 0) mbar_arrive(sb + SM_BAR + BAR_Q + i * 8);
            STAMP(lane == 0 && i == 0, 2);
        }
        STAMP(lane == 0, 21);
        if (hasSlice && lane == 0) {
            mbar_wait(sb + SM_BAR + BAR_PDONE, 0);
#pragma unroll 1
            for (int p = 0; p < 12; p++) {
                const bool uv = p < 4;
                const int r = uv ? p * 128 : (p - 4) * 64;
                if (!uv || late)
                    wait_ticket(smem + SM_BAR + W_PROG, NT + (uv ? YV + (p * DV >> 1) : YW + ((p - 4) * DW >> 1) + (p == 11 ? DL : 0)));
                STAMP(p == 4, 10);
                const uint32_t bar = sb + SM_BAR + BAR_S + (p < 11 ? p >> 1 : 6) * 8;
                if (!(p & 1) || p == 11) mbar_expect_tx(bar, p < 10 ? 16384 : 8192);
                tma_2d(sb + SM_SQ + p * 8192, uv ? &M.m_uv[late] : &M.m_w[mat], uv ? j * 32 : cg * 64,
                       uv ? r : (rg + 8 * (r >> 7)) * 128 + (r & 127), bar, pol);
            }
        }
    } else if (warp >= 4) {
        const int wi = warp - 4;
        const uint32_t slot = sb + SM_SLOT + wi * 32768;
        const uint32_t bar = sb + SM_BAR + BAR_FULL + wi * 16, barV = bar + 8;
        unsigned tk = wi * NA_CTA + cta;
        const int ev = wi;
        if (lane == 0) {
            if (wi) mbar_init(bar, 1);
            mbar_init(barV, 1);
            if (isB && wi == 0) {
                for (int s = 0; s < 5; s++) {
                    mbar_init(sb + SM_BAR + BAR_BFULL + s * 8, 1);
                    mbar_init(sb + SM_BAR + BAR_BEMPTY + s * 8, 4);
                }
            }
            asm volatile("fence.mbarrier_init.release.cluster;" ::: "memory");
        }
        __syncthreads();
        const uint32_t epoch = *(volatile uint32_t*)(smem + SM_BAR + W_EPOCH);
        const uint32_t tag = (epoch + 1) & 1;

        bool active = true;
        if (isB) {
            if (wi == 1 && lane == 0) {
                wait_counter(&G.cntQabs.v, (epoch + 1) * 128, 64);
                fence_proxy_async();
                mbar_expect_tx(sb + SM_BAR + BAR_QABS, 32768);
                bulk_load_nohint(sb + SM_SLOT + 5 * 32768, G.qabs + ((cta - NA_CTA) >> 3) * 16384, 32768, sb + SM_BAR + BAR_QABS);
            }
            if (wi == 0 && lane == 0) {
                const int ib = cta - NA_CTA;
                int s = 0, sl = 0; uint32_t ph = 1, phl = 0;
                for (int u = 0; u < 32; u++) {
                    if (u >= BINFL) {
                        mbar_wait(sb + SM_BAR + BAR_BFULL + sl * 8, phl);
                        LAND(true, 16384 + ib * 32 + u);
                        if (++sl == 5) { sl = 0; phl ^= 1; }
                    }
                    if (u == 3 && hasSlice) mbar_wait(sb + SM_BAR + BAR_WFREE, 0);
                    mbar_wait(sb + SM_BAR + BAR_BEMPTY + s * 8, ph);
                    const uint32_t fb = sb + SM_BAR + BAR_BFULL + s * 8;
                    const int row = (ib >> 3) * 8192 + ((u >> 1) * 8 + (ib & 7)) * 64;
                    mbar_expect_tx(fb, 32768);
                    for (int x = 0; x < 4; x++)
                        tma_2d(sb + SM_SLOT + s * 32768 + x * 8192, &M.m_ckv, ((u & 1) * 4 + x) * 64, row, fb, pol);
                    if (++s == 5) { s = 0; ph ^= 1; }
                }
            }
            __syncwarp();
            mbar_wait(sb + SM_BAR + BAR_BDONE, 0);
            if (lane == 0) tk = NSTATIC + atomicInc(&G.ticket.v, DRAWS - 1);
            tk = __shfl_sync(~0u, tk, 0);
            active = tk < NT;
        } else if (ev != 0) {
            __syncwarp();
            mbar_wait(sb + SM_BAR + BAR_W + (ev - 1) * 8, 0);
        }
        if (active) {
            if ((isB || ev != 0) && lane == 0) {
                mbar_expect_tx(bar, 16384);
                bulk_load(slot, (const char*)P.K + (size_t)tk * 16384, 16384, bar, pol);
            }
            const uint32_t kA = slot + g * 256 + t * 16 + (g & 1) * 64, kB = kA ^ 64;
            const uint32_t qo = t * 16 + ((g >> 1) & 1) * 64 + (g & 1) * 8;
            const uint32_t v0 = slot + 16384 + (2 * t) * 128 + ((g ^ (2 * t)) << 4), v1 = (v0 + 128) ^ 16;
            const uint32_t sl0 = (g & 1) ? 0x1044u : 0x4410u, sl1 = (g & 1) ? 0x3244u : 0x4432u;
            const uint32_t sa0 = (g & 2) ? 0x4444u : sl0, sa1 = (g & 2) ? 0x4444u : sl1;
            const uint32_t sb0 = (g & 2) ? sl0 : 0x4444u, sb1 = (g & 2) ? sl1 : 0x4444u;
            const int d0 = 64 * (t >> 1) + 8 * g + 4 * (t & 1);
            uint32_t ph = 0;
            while (true) {
                const uint32_t qa = sb + SM_QA + (tk >> 7) * 256 + qo;
                bool vout = false;
                if (XRV && lane == 0 && tk >= NT - XRV && !mbar_wait_for(bar, ph, TV)) {
                    mbar_expect_tx(barV, 16384);
                    tma_3d(slot + 16384, &M.m_v, tk * 64, 0, barV, pol);
                    vout = true;
                }
                if (XRV) __syncwarp();
                mbar_wait(bar, ph);
                LAND(lane == 0, tk);
                unsigned nxt = 0;
                if (lane == 0) {
                    if (!vout) {
                        mbar_expect_tx(barV, 16384);
                        tma_3d(slot + 16384, &M.m_v, tk * 64, 0, barV, pol);
                    }
                    asm volatile("atom.relaxed.gpu.global.inc.u32 %0, [%1], %2;" : "=r"(nxt) : "l"(&G.ticket.v), "r"(DRAWS - 1) : "memory");
                }
                __syncwarp();
                mbar_wait(sb + SM_BAR + BAR_Q + (tk >> 10) * 8, 0);
                STAMP(tid == 128 && tk < NSTATIC, 3);
                uint2 qf[4];
                qf[0] = lds64(qa); qf[1] = lds64(qa ^ 64); qf[2] = lds64(qa + 128); qf[3] = lds64((qa ^ 64) + 128);
                float c[8][4];
#pragma unroll
                for (int i = 0; i < 32; i++) (&c[0][0])[i] = 0.f;
#pragma unroll
                for (int s = 0; s < 4; s++)
#pragma unroll
                    for (int jj = 0; jj < 8; jj++) {
                        const uint4 u = lds128(((s & 1) ? kB : kA) + jj * 2048 + (s >> 1) * 128);
                        mma16816(c[jj], u.x, u.y, u.z, u.w, qf[s].x, qf[s].y);
                    }
                float sc[8];
#pragma unroll
                for (int jj = 0; jj < 8; jj++) sc[jj] = c[jj][0] + c[jj][3];
#pragma unroll
                for (int jj = 0; jj < 8; jj += 2) scale_scores(sc[jj], sc[jj + 1]);
                float m = fmaxf(fmaxf(fmaxf(sc[0], sc[1]), fmaxf(sc[2], sc[3])), fmaxf(fmaxf(sc[4], sc[5]), fmaxf(sc[6], sc[7])));
                m = fmaxf(m, __shfl_xor_sync(~0u, m, 5));
                m = fmaxf(m, __shfl_xor_sync(~0u, m, 8));
                m = fmaxf(m, __shfl_xor_sync(~0u, m, 16));
                const float ms = __uint_as_float(tagw(m * LOG2E, tag));
                uint32_t W0[4], W1[4];
                float l = 0.f;
#pragma unroll
                for (int i = 0; i < 4; i++) {
                    const uint32_t pp = pack_bf16(ex2(fmaf(sc[2 * i], LOG2E, -ms)), ex2(fmaf(sc[2 * i + 1], LOG2E, -ms)));
                    W0[i] = __shfl_sync(~0u, pp, 8 * t);
                    W1[i] = __shfl_sync(~0u, pp, 8 * t + 5);
                    l += bf_lo(pp) + bf_hi(pp);
                }
                l += __shfl_xor_sync(~0u, l, 5);
                l += __shfl_xor_sync(~0u, l, 8);
                l += __shfl_xor_sync(~0u, l, 16);
                if (lane == 0 || lane == 2)
                    st_relaxed128((char*)G.partML + tk * 32 + lane * 8, __float_as_uint(ms), tagw(l, tag), __float_as_uint(ms), tagw(l, tag));
                uint32_t pb[16][2];
#pragma unroll
                for (int i = 0; i < 16; i++) {
                    const uint32_t pw = (i & 1) ? W1[i >> 2] : W0[i >> 2];
                    pb[i][0] = prmt(pw, 0, (i & 2) ? sa1 : sa0);
                    pb[i][1] = prmt(pw, 0, (i & 2) ? sb1 : sb0);
                    asm volatile("" : "+r"(pb[i][0]), "+r"(pb[i][1]));
                }
                float* po = G.partO + (size_t)tk * 128 + d0;
                asm volatile("" : "+l"(po));
                if (lane == 0) note_draw(smem + SM_BAR + W_PROG, nxt);
                nxt += NSTATIC;
                if (nxt >= NT - XPK && nxt < NT && lane == 0) {
                    mbar_expect_tx(bar, 16384);
                    bulk_load(slot, (const char*)P.K + (size_t)nxt * 16384, 16384, bar, pol);
                }
                mbar_wait(barV, ph);
                LAND(lane == 0, 8192 + tk);
                ph ^= 1;
                if (nxt < NT - XPK && lane == 0) {
                    mbar_expect_tx(bar, 16384);
                    bulk_load(slot, (const char*)P.K + (size_t)nxt * 16384, 16384, bar, pol);
                }
                __syncwarp();
                float acc[2][4][4];
#pragma unroll
                for (int i = 0; i < 32; i++) (&acc[0][0][0])[i] = 0.f;
#pragma unroll
                for (int jj = 0; jj < 8; jj++)
#pragma unroll
                    for (int e = 0; e < 2; e++)
#pragma unroll
                        for (int hh = 0; hh < 2; hh++) {
                            const uint4 u = lds128((e ? v1 : v0) + jj * 1024 + hh * 8192);
                            mma16816(acc[hh][(jj & 1) * 2 + e], u.x, u.y, u.z, u.w, pb[2 * jj + e][0], pb[2 * jj + e][1]);
                        }
                float r4[4];
#pragma unroll
                for (int i = 0; i < 4; i++) {
                    const float x0 = (acc[0][0][i] + acc[0][1][i]) + (acc[0][2][i] + acc[0][3][i]);
                    const float x1 = (acc[1][0][i] + acc[1][1][i]) + (acc[1][2][i] + acc[1][3][i]);
                    r4[i] = (t & 2) ? x1 : x0;
                }
                st_relaxed128(po, tagw(r4[0], tag), tagw(r4[1], tag), tagw(r4[2], tag), tagw(r4[3], tag));
                nxt = __shfl_sync(~0u, nxt, 0);
                if (nxt >= NT) break;
                tk = nxt;
            }
            STAMP(lane == 0, 16 + wi);
        } else if (lane == 0) {
            note_draw(smem + SM_BAR + W_PROG, tk - NSTATIC);
        }
    } else {
        float* red = (float*)(smem + SM_RED2);
        if (tid == 32) {
            const uint32_t ep0 = ld_relaxed32(&G.epoch.v);
            for (int e = 0; e < 8; e++) mbar_init(sb + SM_BAR + BAR_Q + e * 8, 1);
            for (int e = 1; e < 10; e++) mbar_init(sb + SM_BAR + BAR_W + e * 8, 1);
            mbar_init(sb + SM_BAR + BAR_BDONE, 1);
            mbar_init(sb + SM_BAR + BAR_PDONE, 1);
            mbar_init(sb + SM_BAR + BAR_QABS, 1);
            mbar_init(sb + SM_BAR + BAR_WFREE, 1);
            asm volatile("fence.mbarrier_init.release.cluster;" ::: "memory");
            asm volatile("st.volatile.shared.v4.u32 [%0], {%1, %2, %1, %1};" ::"r"(sb + SM_BAR + W_PROG), "r"(0), "r"(now_ns()) : "memory");
            *(volatile uint32_t*)(smem + SM_BAR + W_EPOCH) = ep0;
        } else if (tid == 64) {
            asm volatile("prefetch.tensormap [%0];" ::"l"(&M.m_v) : "memory");
            asm volatile("prefetch.tensormap [%0];" ::"l"(&M.m_wqB) : "memory");
            asm volatile("prefetch.tensormap [%0];" ::"l"(&M.m_wuk) : "memory");
        }
        __syncthreads();
        const uint32_t epoch = *(volatile uint32_t*)(smem + SM_BAR + W_EPOCH);
        const uint32_t tag = (epoch + 1) & 1;
        STAMP(tid == 0, 14);

        if (hasSlice) {
            const uint32_t nt = tag ^ 1;
            const int qoff = ((tid >> 5) & 1) * 4096 + 32 * j + (tid & 31);
            if (tid < 64) {
                st_relaxed32(G.qA + qoff, nt); st_relaxed32(G.qB + qoff, nt);
                if (tid < 32) {
                    st_relaxed32(G.o + 32 * j + tid, nt); st_relaxed32(G.o + 4096 + 32 * j + tid, nt);
                    st_relaxed32(G.ctx + 32 * j + tid, nt); st_relaxed32(G.ctx + 4096 + 32 * j + tid, nt);
                }
            }
            if (tid >= 64 && tid < 72) st_relaxed32((uint32_t*)P.out + 8 * j + (tid - 64), 0);
            mbar_wait(sb + SM_BAR + BAR_W, 0);
            LAND(tid == 0, 17408 + 0 * 128 + j);
            if (tid == 96) {
                mbar_expect_tx(sb + SM_BAR + BAR_W + 8, 32768);
                issue_tall(sb + SM_WQB, &M.m_wqB, j * 32, 0, sb + SM_BAR + BAR_W + 8, pol);
            }
            __syncwarp();
            STAMP(tid == 0, 15);
            uint2 bf[16];
            tall_prep(bf, sb + SM_P, warp, g, t);
            gemv_tall(sb + SM_WQ, bf, (float*)(smem + SM_RED1), warp, g, t);
            tall_finish((float*)(smem + SM_RED1), G.qA + qoff, tid, tag, 0, h >= HCLR ? 32 : 64);
            STAMP(tid == 0, 1);
            tall_prep(bf, sb + SM_P + 2048, warp, g, t);
            mbar_wait(sb + SM_BAR + BAR_W + 8, 0);
            LAND(tid == 0, 17408 + 1 * 128 + j);
            if (tid == 96) {
                mbar_expect_tx(sb + SM_BAR + BAR_W + 16, 32768);
                tma_2d(sb + SM_WUK, &M.m_wuk, h * 128, qd * 128, sb + SM_BAR + BAR_W + 16, pol);
            }
            __syncwarp();
            gemv_tall(sb + SM_WQB, bf, red, warp, g, t);
            tall_finish(red, G.qB + qoff, tid, tag);
            if (tid == 96) mbar_arrive(sb + SM_BAR + BAR_WFREE);
            STAMP(tid == 0, 25);
            named_bar(1, 128);
            uint4 qf[4];
            {
                const float* qp = G.qB + ((g & 1) * 32 + h) * 128 + t * 8;
                uint4 v[8];
                unsigned it = 0;
                while (true) {
                    uint32_t bad = 0;
#pragma unroll
                    for (int i = 0; i < 8; i++) v[i] = ld_relaxed128(qp + (i >> 1) * 32 + (i & 1) * 4);
#pragma unroll
                    for (int i = 0; i < 8; i++) bad |= bad4(v[i], tag);
                    if (!__any_sync(~0u, bad & 1u)) break;
                    __nanosleep(100);
                    if (++it > SPIN_LIMIT) __trap();
                }
#pragma unroll
                for (int s = 0; s < 4; s++)
                    qf[s] = make_uint4(pack_bf16(__uint_as_float(v[2 * s].x), __uint_as_float(v[2 * s].y)),
                                       pack_bf16(__uint_as_float(v[2 * s].z), __uint_as_float(v[2 * s].w)),
                                       pack_bf16(__uint_as_float(v[2 * s + 1].x), __uint_as_float(v[2 * s + 1].y)),
                                       pack_bf16(__uint_as_float(v[2 * s + 1].z), __uint_as_float(v[2 * s + 1].w)));
            }
            mbar_wait(sb + SM_BAR + BAR_W + 16, 0);
            LAND(tid == 0, 17408 + 2 * 128 + j);
#pragma unroll
            for (int jj = 0; jj < 2; jj++) {
                float c[4] = {0.f, 0.f, 0.f, 0.f};
#pragma unroll
                for (int s = 0; s < 4; s++) {
                    const uint32_t a = sb + SM_WUK + (32 * warp + 16 * jj + g) * 256 + (t + 4 * s) * 16;
                    const uint4 u = lds128(a), v = lds128(a + 2048);
                    mma16816(c, u.x, v.x, u.y, v.y, qf[s].x, qf[s].y);
                    mma16816(c, u.z, v.z, u.w, v.w, qf[s].z, qf[s].w);
                }
                const float val = (t & 2) ? ((t & 1) ? c[3] : c[2]) : ((t & 1) ? c[1] : c[0]);
                const int cc = 128 * qd + 32 * warp + 16 * jj + g + ((t & 2) ? 8 : 0);
                const int off = (cc >> 6) * 2048 + h * 64 + ((((cc & 63) >> 3) ^ (h & 7)) << 3) + (cc & 7);
                G.qabs[(t & 1) * 16384 + off] = __float2bfloat16(val);
            }
            named_bar(1, 128);
            if (tid == 0) red_release(&G.cntQabs.v);
            STAMP(tid == 0, 4);
            if (h >= HCLR) {
#pragma unroll
                for (int k = 0; k < 8; k++)
                    st_relaxed128(G.partO + (size_t)((32 + h) * 128 + 16 * k + (tid >> 3)) * 128 + qd * 32 + (tid & 7) * 4, nt, nt, nt, nt);
                if (tid < 64) st_relaxed128((char*)G.partML + ((32 + h) * 128 + qd * 32) * 32 + tid * 16, nt, nt, nt, nt);
                __threadfence();
                tall_finish((float*)(smem + SM_RED1), G.qA + qoff, tid, tag, 32, 64);
            }
        }

        if (isB) {
            const int ib = cta - NA_CTA;
            float acc[8][16];
#pragma unroll
            for (int i = 0; i < 8; i++)
#pragma unroll
                for (int k = 0; k < 16; k++) acc[i][k] = 0.f;
            float mrun[8], lrun[8];
#pragma unroll
            for (int i = 0; i < 8; i++) { mrun[i] = -INFINITY; lrun[i] = 0.f; }
            const uint64_t dQ = make_desc(sb + SM_SLOT + 5 * 32768);
            const uint64_t dP = make_desc(sb + SM_P);
            const uint32_t pst = sb + SM_P + (((lane >> 4) * 8 + (lane & 7)) * 128) + (((2 * warp + ((lane >> 3) & 1)) ^ (lane & 7)) << 4);
            mbar_wait(sb + SM_BAR + BAR_QABS, 0);
            STAMP(tid == 0, 5);
            int s0 = 0; uint32_t ph0 = 0;
            for (int it = 0; it < 16; it++) {
                int s1 = s0 + 1; uint32_t ph1 = ph0;
                if (s1 == 5) { s1 = 0; ph1 ^= 1; }
                const uint64_t dA0 = make_desc(sb + SM_SLOT + s0 * 32768), dA1 = make_desc(sb + SM_SLOT + s1 * 32768);
                float S[16];
                mbar_wait(sb + SM_BAR + BAR_BFULL + s0 * 8, ph0);
                mbar_wait(sb + SM_BAR + BAR_BFULL + s1 * 8, ph1);
                wg_fence();
#pragma unroll
                for (int k = 0; k < 32; k++) {
                    const uint64_t da = ((k < 16) ? dA0 : dA1) + (uint64_t)((((k >> 2) & 3) * 8192 + (k & 3) * 32) >> 4);
                    const uint64_t db = dQ + (uint64_t)(((k >> 2) * 4096 + (k & 3) * 32) >> 4);
                    wgmma_n32<0>(S, da, db, k > 0);
                }
                wg_commit();
                wg_wait<0>();
#pragma unroll
                for (int i = 0; i < 16; i++) S[i] *= SCALE;
                float mx[8];
#pragma unroll
                for (int i = 0; i < 8; i++) {
                    mx[i] = fmaxf(S[4 * (i >> 1) + (i & 1)], S[4 * (i >> 1) + 2 + (i & 1)]);
                    mx[i] = fmaxf(mx[i], __shfl_xor_sync(~0u, mx[i], 4));
                    mx[i] = fmaxf(mx[i], __shfl_xor_sync(~0u, mx[i], 8));
                    mx[i] = fmaxf(mx[i], __shfl_xor_sync(~0u, mx[i], 16));
                }
                if (g == 0) {
#pragma unroll
                    for (int jb = 0; jb < 4; jb++)
                        *(float2*)(red + warp * 32 + 8 * jb + 2 * t) = make_float2(mx[2 * jb], mx[2 * jb + 1]);
                }
                named_bar(1, 128);
                float al[8];
                bool chg = false;
                uint32_t R[8];
#pragma unroll
                for (int jb = 0; jb < 4; jb++) {
                    float2 a = *(float2*)(red + 8 * jb + 2 * t), b = *(float2*)(red + 32 + 8 * jb + 2 * t);
                    float2 c = *(float2*)(red + 64 + 8 * jb + 2 * t), d = *(float2*)(red + 96 + 8 * jb + 2 * t);
                    const float n0 = fmaxf(mrun[2 * jb], fmaxf(fmaxf(a.x, b.x), fmaxf(c.x, d.x)) * LOG2E);
                    const float n1 = fmaxf(mrun[2 * jb + 1], fmaxf(fmaxf(a.y, b.y), fmaxf(c.y, d.y)) * LOG2E);
                    chg |= (n0 != mrun[2 * jb]) | (n1 != mrun[2 * jb + 1]);
                    al[2 * jb] = ex2(mrun[2 * jb] - n0);
                    al[2 * jb + 1] = ex2(mrun[2 * jb + 1] - n1);
                    mrun[2 * jb] = n0; mrun[2 * jb + 1] = n1;
                    R[2 * jb]     = pack_bf16(ex2(fmaf(S[4 * jb], LOG2E, -n0)), ex2(fmaf(S[4 * jb + 1], LOG2E, -n1)));
                    R[2 * jb + 1] = pack_bf16(ex2(fmaf(S[4 * jb + 2], LOG2E, -n0)), ex2(fmaf(S[4 * jb + 3], LOG2E, -n1)));
                    lrun[2 * jb]     = fmaf(lrun[2 * jb], al[2 * jb], bf_lo(R[2 * jb]) + bf_lo(R[2 * jb + 1]));
                    lrun[2 * jb + 1] = fmaf(lrun[2 * jb + 1], al[2 * jb + 1], bf_hi(R[2 * jb]) + bf_hi(R[2 * jb + 1]));
                }
                asm volatile("stmatrix.sync.aligned.m8n8.x4.trans.shared.b16 [%0], {%1,%2,%3,%4};"
                             ::"r"(pst), "r"(R[0]), "r"(R[1]), "r"(R[2]), "r"(R[3]) : "memory");
                asm volatile("stmatrix.sync.aligned.m8n8.x4.trans.shared.b16 [%0], {%1,%2,%3,%4};"
                             ::"r"(pst + 2048), "r"(R[4]), "r"(R[5]), "r"(R[6]), "r"(R[7]) : "memory");
                asm volatile("fence.proxy.async.shared::cta;" ::: "memory");
                if (__any_sync(~0u, chg)) {
#pragma unroll
                    for (int mt = 0; mt < 8; mt++)
#pragma unroll
                        for (int k = 0; k < 16; k++) acc[mt][k] *= al[2 * (k >> 2) + (k & 1)];
                }
                named_bar(1, 128);
                wg_fence();
#pragma unroll
                for (int mt = 0; mt < 4; mt++)
#pragma unroll
                    for (int kk = 0; kk < 4; kk++)
                        wgmma_n32<1>(acc[mt], dA0 + (uint64_t)((mt * 8192 + kk * 2048) >> 4), dP + (uint64_t)((kk * 32) >> 4), 1);
                wg_commit();
#pragma unroll
                for (int mt = 0; mt < 4; mt++)
#pragma unroll
                    for (int kk = 0; kk < 4; kk++)
                        wgmma_n32<1>(acc[4 + mt], dA1 + (uint64_t)((mt * 8192 + kk * 2048) >> 4), dP + (uint64_t)((kk * 32) >> 4), 1);
                wg_commit();
                wg_wait<1>();
                if (lane == 0) mbar_arrive(sb + SM_BAR + BAR_BEMPTY + s0 * 8);
                wg_wait<0>();
                if (lane == 0) mbar_arrive(sb + SM_BAR + BAR_BEMPTY + s1 * 8);
                s0 = s1 + 1; ph0 = ph1;
                if (s0 == 5) { s0 = 0; ph0 ^= 1; }
            }
#pragma unroll
            for (int i = 0; i < 8; i++) {
                lrun[i] += __shfl_xor_sync(~0u, lrun[i], 4);
                lrun[i] += __shfl_xor_sync(~0u, lrun[i], 8);
                lrun[i] += __shfl_xor_sync(~0u, lrun[i], 16);
            }
            if (g == 0) {
#pragma unroll
                for (int jb = 0; jb < 4; jb++) {
                    *(float2*)(red + 128 + warp * 32 + 8 * jb + 2 * t) = make_float2(lrun[2 * jb], lrun[2 * jb + 1]);
                    if (warp == 0) *(float2*)(red + 256 + 8 * jb + 2 * t) = make_float2(mrun[2 * jb], mrun[2 * jb + 1]);
                }
            }
            named_bar(1, 128);
            if (tid == 0) mbar_arrive(sb + SM_BAR + BAR_BDONE);
            if (tid < 32)
                G.bml[ib * 32 + tid] = make_float2(red[256 + tid], red[128 + tid] + red[160 + tid] + red[192 + tid] + red[224 + tid]);
            float* bp = G.bpart + (size_t)ib * 16384 + (2 * t) * 512 + 16 * warp + g;
#pragma unroll
            for (int mt = 0; mt < 8; mt++)
#pragma unroll
                for (int k = 0; k < 16; k++)
                    bp[(8 * (k >> 2) + (k & 1)) * 512 + 64 * mt + ((k >> 1) & 1) * 8] = acc[mt][k];
            named_bar(1, 128);
            if (tid == 0) red_release(&G.cntB.v);
            STAMP(tid == 0, 6);
        }

        if (hasSlice) {
            if (tid == 0) {
                wait_prog(smem + SM_BAR + W_PROG, TUV);
                wait_counter(&G.cntB.v, (epoch + 1) * NB_CTA, 500);
                if (cta == 0) st_relaxed32(&G.epoch.v, epoch + 1);
                asm volatile("prefetch.tensormap [%0];" ::"l"(&M.m_uv[late]) : "memory");
                asm volatile("prefetch.tensormap [%0];" ::"l"(&M.m_w[mat]) : "memory");
            }
            named_bar(1, 128);
            if (tid == 32) mbar_arrive(sb + SM_BAR + BAR_PDONE);
            STAMP(tid == 0, 7);
            {
                const int b = tid >> 6, cp = tid & 63;
                uint2 ml[8];
#pragma unroll
                for (int i = 0; i < 8; i++) ml[i] = ld_relaxed64(G.bml + (b * 8 + i) * 32 + h);
                uint4 pv[2][8];
#pragma unroll
                for (int i = 0; i < 16; i++)
                    pv[i >> 3][i & 7] = ld_relaxed128(G.bpart + (size_t)(b * 8 + (i & 7)) * 16384 + h * 512 + (i >> 3) * 256 + 4 * cp);
                float M = __uint_as_float(ml[0].x);
#pragma unroll
                for (int i = 1; i < 8; i++) M = fmaxf(M, __uint_as_float(ml[i].x));
                float L = 0.f, wgt[8];
#pragma unroll
                for (int i = 0; i < 8; i++) {
                    wgt[i] = ex2(__uint_as_float(ml[i].x) - M);
                    L = fmaf(wgt[i], __uint_as_float(ml[i].y), L);
                }
                const float inv = 1.f / L;
#pragma unroll
                for (int x = 0; x < 2; x++) {
                    float v0 = 0.f, v1 = 0.f, v2 = 0.f, v3 = 0.f;
#pragma unroll
                    for (int i = 0; i < 8; i++) {
                        v0 = fmaf(wgt[i], __uint_as_float(pv[x][i].x), v0);
                        v1 = fmaf(wgt[i], __uint_as_float(pv[x][i].y), v1);
                        v2 = fmaf(wgt[i], __uint_as_float(pv[x][i].z), v2);
                        v3 = fmaf(wgt[i], __uint_as_float(pv[x][i].w), v3);
                    }
                    *(uint2*)(smem + SM_P + b * 1024 + x * 512 + cp * 8) = make_uint2(pack_bf16(v0 * inv, v1 * inv), pack_bf16(v2 * inv, v3 * inv));
                }
            }
            STAMP(tid == 0, 8);
        }
        {
            named_bar(1, 128);
#pragma unroll 1
            for (uint64_t plan = j < 64 ? 0xF7351260ull : (j < 124 ? (late ? 0xF75314260ull : 0xF7514603ull) : (hasSlice ? 0xF753426ull : 0xF10ull));
                 plan != 0xF; plan >>= 4) {
                const int step = plan & 15;
                if ((step & 14) == 4) {
                    const int hh = rg + 8 * warp;
                    const uint32_t real = step & 1, both = real & (mat | (warp != 3));
                    if (both) wait_ticket(smem + SM_BAR + W_PROG, mat ? NT + YB : min((33 + hh) * 128 + LAGT, NT + YLATE) + YX);
                    __syncwarp();
                    const float* src = (mat ? G.ctx : G.o) + hh * 128 + lane * 4;
                    uint4 v[2];
                    v[0] = v[1] = make_uint4(tag, tag, tag, tag);
                    uint32_t bad0 = real, bad1 = both;
                    unsigned it = 0;
                    while (true) {
                        ld_relaxed128_if(v[0], src, bad0);
                        ld_relaxed128_if(v[1], src + 4096, bad1);
                        bad0 = bad4(v[0], tag) & 1u; bad1 = bad4(v[1], tag) & 1u;
                        if (!__any_sync(~0u, bad0 | bad1)) break;
                        if (++it > SPIN_LIMIT) __trap();
                    }
#pragma unroll
                    for (int b = 0; b < 2; b++)
                        *(uint2*)(smem + SM_VEC + V_X + b * XSTR + (128 * warp + 4 * lane) * 2) =
                            make_uint2(pack_bf16(__uint_as_float(v[b].x), __uint_as_float(v[b].y)), pack_bf16(__uint_as_float(v[b].z), __uint_as_float(v[b].w)));
                    named_bar(1, 128);
                    STAMP(tid == 0, 29);
                } else if (step >= 6) {
                    const uint32_t real = step & 1;
                    const uint32_t xa = sb + SM_VEC + V_X + ((lane >> 1) & 1) * XSTR + 8 * (lane >> 3) * 2;
                    const uint32_t wa = sb + SM_SQ + 2 * 16384 + (8 * (lane >> 4) + (lane & 7)) * 128 +
                                        (((2 * warp + ((lane >> 3) & 1)) ^ (lane & 7)) << 4);
                    const uint32_t bs = sb + SM_BAR + BAR_S + 16;
                    const float* src = G.o + 4096 + (24 + rg) * 128 + lane * 4;
                    const uint32_t needx = real & (mat ^ 1);
                    uint32_t* dst = (uint32_t*)P.out + (t & 1) * 512 + mat * 256 + cg * 32 + warp * 8 + (t >> 1) * 4 + (g >> 1);
                    asm volatile("" : "+l"(dst));
                    uint4 v = make_uint4(tag, tag, tag, tag);
                    float d[4][4];
#pragma unroll
                    for (int i = 0; i < 16; i++) (&d[0][0])[i] = 0.f;
#pragma unroll 1
                    for (int u = 0; u < 3; u++) {
                        uint4 xf[4];
                        if (needx && u == 2) wait_ticket(smem + SM_BAR + W_PROG, NT + YP);
                        __syncwarp();
                        ld_relaxed128_if(v, src, needx & (u == 2));
#pragma unroll
                        for (int i = 0; i < 4; i++) xf[i] = ldsm4(xa + u * 256 + i * 64);
                        if (real) mbar_wait_nt(bs + u * 8, 0);
#pragma unroll
                        for (int i = 0; i < 4; i++) {
                            const uint4 w0 = ldsm4t(wa + u * 16384 + i * 4096), w1 = ldsm4t(wa + u * 16384 + i * 4096 + 2048);
                            mma16816(d[(i & 1) * 2], w0.x, w0.y, w0.z, w0.w, xf[i].x, xf[i].y);
                            mma16816(d[(i & 1) * 2 + 1], w1.x, w1.y, w1.z, w1.w, xf[i].z, xf[i].w);
                        }
                    }
                    unsigned it = 0;
                    while (__any_sync(~0u, bad4(v, tag) & 1u)) {
                        if (++it > SPIN_LIMIT) __trap();
                        v = ld_relaxed128(src);
                    }
                    STAMP(tid == 96, 20);
                    if (!mat)
                        *(uint2*)(smem + SM_VEC + V_X + XSTR + (384 + 4 * lane) * 2) =
                            make_uint2(pack_bf16(__uint_as_float(v.x), __uint_as_float(v.y)), pack_bf16(__uint_as_float(v.z), __uint_as_float(v.w)));
                    __syncwarp();
                    uint4 xf[4], w[4];
#pragma unroll
                    for (int i = 0; i < 4; i++) xf[i] = ldsm4(xa + 3 * 256 + i * 64);
#pragma unroll
                    for (int q = 0; q < 2; q++) {
                        if (q) {
#pragma unroll
                            for (int i = 0; i < 4; i++) {
                                d[0][i] = (d[0][i] + d[1][i]) + (d[2][i] + d[3][i]);
                                d[1][i] = d[2][i] = d[3][i] = 0.f;
                            }
                        }
                        if (real) mbar_wait_nt(bs + 24 + q * 8, 0);
#pragma unroll
                        for (int i = 0; i < 4; i++) w[i] = ldsm4t(wa + 3 * 16384 + q * 8192 + i * 2048);
#pragma unroll
                        for (int i = 0; i < 2; i++) {
                            mma16816(d[2 * i], w[2 * i].x, w[2 * i].y, w[2 * i].z, w[2 * i].w, xf[2 * q + i].x, xf[2 * q + i].y);
                            mma16816(d[2 * i + 1], w[2 * i + 1].x, w[2 * i + 1].y, w[2 * i + 1].z, w[2 * i + 1].w, xf[2 * q + i].z, xf[2 * q + i].w);
                        }
                    }
                    STAMP(tid == 64, 22);
                    float e[4];
#pragma unroll
                    for (int i = 0; i < 4; i++) e[i] = (t & 2) ? d[i][2] : d[i][0];
                    red_out(dst, ((e[0] + e[1]) + e[2]) + e[3], g, real);
                    STAMP(tid == 64, 13);
                    if (real) asm volatile("exit;");
                } else if (step >= 2) {
                    uint2 bf[16];
                    tall_prep(bf, sb + SM_P, warp, g, t);
                    if (step & 1) mbar_wait(sb + SM_BAR + BAR_S + (warp >> 1) * 8, 0);
                    LAND(tid == 64, 17408 + 3 * 128 + j);
                    gemv_tall(sb + SM_SQ, bf, red + 512, warp, g, t);
                    tall_finish(red + 512, G.ctx + ((tid >> 5) & 1) * 4096 + 32 * j + (tid & 31), tid, tag, 0, (step & 1) ? 64 : 0);
                    STAMP(tid == 0, 12);
                } else {
                    const int b = step;
                    const int hm = min(h, 31), bh = 32 * b + hm;
                    wait_ticket(smem + SM_BAR + W_PROG, min((bh + 1) * 128 + LAGT, NT + YLATE + max(hm - 27, 0) * YSL));
                    __syncwarp();
                    float* rb = red + b * 256;
                    combineA(G, bh, qd, tag, rb, tid, smem + SM_BAR + W_PROG);
                    {
                        if (tid < 32)
                            st_relaxed32(G.o + bh * 128 + 32 * qd + tid, tagw((rb[tid] + rb[32 + tid]) + (rb[64 + tid] + rb[96 + tid]), tag));
                        STAMP(tid == 0, 9 + 2 * b);
                    }
                }
            }
        }
    }
}

typedef CUresult (*EncodeFn)(CUtensorMap*, CUtensorMapDataType, cuuint32_t, void*, const cuuint64_t*, const cuuint64_t*,
                             const cuuint32_t*, const cuuint32_t*, CUtensorMapInterleave, CUtensorMapSwizzle,
                             CUtensorMapL2promotion, CUtensorMapFloatOOBfill);

}

extern "C" void kernel_launch(void* const* d_in, const int* in_sizes, int n_in, void* d_out, int out_size) {
    (void)in_sizes; (void)n_in; (void)out_size;
    static EncodeFn encode = nullptr;
    static void* scratch = nullptr;
    if (!encode) {
        void* fn = nullptr;
        cudaDriverEntryPointQueryResult st;
        cudaGetDriverEntryPoint("cuTensorMapEncodeTiled", &fn, cudaEnableDefault, &st);
        encode = (EncodeFn)fn;
        cudaGetSymbolAddress(&scratch, g_raw);
        cudaFuncSetAttribute(fused_decode_kernel, cudaFuncAttributeMaxDynamicSharedMemorySize, SM_TOTAL);
    }
    Ptrs P;
    Maps M;
    auto mk = [&](CUtensorMap* m, void* ptr, cuuint64_t cols, cuuint64_t rows, cuuint32_t bc, cuuint32_t br, CUtensorMapSwizzle sw,
                  CUtensorMapL2promotion promo) {
        const cuuint64_t gdim[2] = {cols, rows};
        const cuuint64_t gstr[1] = {cols * 2};
        const cuuint32_t box[2] = {bc, br};
        const cuuint32_t estr[2] = {1, 1};
        encode(m, CU_TENSOR_MAP_DATA_TYPE_BFLOAT16, 2, ptr, gdim, gstr, box, estr, CU_TENSOR_MAP_INTERLEAVE_NONE, sw,
               promo, CU_TENSOR_MAP_FLOAT_OOB_FILL_NONE);
    };
    mk(&M.m_wq, d_in[3], 4096, 512, 32, 256, CU_TENSOR_MAP_SWIZZLE_64B, CU_TENSOR_MAP_L2_PROMOTION_NONE);
    auto mk3 = [&](CUtensorMap* m, void* ptr, cuuint64_t cols, cuuint64_t rows) {
        const cuuint64_t gdim[3] = {64, rows, cols / 64};
        const cuuint64_t gstr[2] = {cols * 2, 128};
        const cuuint32_t box[3] = {64, 64, 2};
        const cuuint32_t estr[3] = {1, 1, 1};
        encode(m, CU_TENSOR_MAP_DATA_TYPE_BFLOAT16, 3, ptr, gdim, gstr, box, estr, CU_TENSOR_MAP_INTERLEAVE_NONE,
               CU_TENSOR_MAP_SWIZZLE_128B, CU_TENSOR_MAP_L2_PROMOTION_L2_256B, CU_TENSOR_MAP_FLOAT_OOB_FILL_NONE);
    };
    mk3(&M.m_v, d_in[2], 128, 524288);
    mk(&M.m_uv[0], d_in[9], 4096, 512, 32, 128, CU_TENSOR_MAP_SWIZZLE_64B, CU_TENSOR_MAP_L2_PROMOTION_NONE);
    mk(&M.m_uv[1], d_in[9], 4096, 512, 32, 128, CU_TENSOR_MAP_SWIZZLE_64B, CU_TENSOR_MAP_L2_PROMOTION_L2_256B);
    mk(&M.m_w[0], d_in[4], 512, 4096, 64, 64, CU_TENSOR_MAP_SWIZZLE_128B, CU_TENSOR_MAP_L2_PROMOTION_L2_256B);
    mk(&M.m_w[1], d_in[10], 512, 4096, 64, 64, CU_TENSOR_MAP_SWIZZLE_128B, CU_TENSOR_MAP_L2_PROMOTION_L2_256B);
    mk(&M.m_ckv, d_in[6], 512, 16384, 64, 64, CU_TENSOR_MAP_SWIZZLE_128B, CU_TENSOR_MAP_L2_PROMOTION_L2_256B);
    mk(&M.m_wqB, d_in[7], 4096, 512, 32, 256, CU_TENSOR_MAP_SWIZZLE_64B, CU_TENSOR_MAP_L2_PROMOTION_NONE);
    mk(&M.m_wuk, d_in[8], 4096, 512, 128, 128, CU_TENSOR_MAP_SWIZZLE_NONE, CU_TENSOR_MAP_L2_PROMOTION_L2_256B);
    P.xA = (const __nv_bfloat16*)d_in[0];
    P.K = (const __nv_bfloat16*)d_in[1];
    P.xB = (const __nv_bfloat16*)d_in[5];
    P.out = (__nv_bfloat16*)d_out;
    P.g = (Scratch*)scratch;
    cudaLaunchConfig_t cfg = {};
    cfg.gridDim = dim3(GRID);
    cfg.blockDim = dim3(NTHREADS);
    cfg.dynamicSmemBytes = SM_TOTAL;
    cfg.stream = cudaStreamPerThread;
    cudaLaunchAttribute attr;
    attr.id = cudaLaunchAttributeCooperative;
    attr.val.cooperative = 1;
    cfg.attrs = &attr;
    cfg.numAttrs = 1;
    cudaLaunchKernelEx(&cfg, fused_decode_kernel, P, M);
}
```

```cpp
#include <cuda_runtime.h>
#include <cuda_bf16.h>
#include <cuda.h>
#include <stdint.h>

namespace {

constexpr int NT       = 8192;
constexpr int GRID     = 132;
constexpr int NB_CTA   = 16;
constexpr int NA_CTA   = GRID - NB_CTA;
constexpr int NWORK    = 3;
#define YV 292
#define DV 56
#define YW 407
#define DW 68
#define DL 6
#define YX 150
#define YB 582
#define YP 605
#define XRV 330
#define TV 3200
#define PFB 8192
#define LAGT 1060
#define YLATE 120
#define YSL 70
#define YO 450
#define YOS 40
#define TUV (43 * 128)
#define XPK 80
#define FRZ 300
#define GN 8
#define GST 16
#define GLOOK 120
#define SLP 60
#define SLT 20
#define NSL 20
#define QDELAY 500
constexpr int NEARX = 400;
constexpr int JE0   = 112;
constexpr int HCLR  = 26;
constexpr int BINFL = 2;
constexpr int NSTATIC  = NA_CTA * NWORK;
constexpr unsigned DRAWS = (NT - NSTATIC) + GRID * NWORK;
static_assert(52 * 128 + LAGT + 300 <= NT && TUV + 10 * 128 <= NT, "wait_prog thresholds must be reachable");
constexpr int NTHREADS = 256;
constexpr float SCALE = 0.08838834764831845f, LOG2E = 1.4426950408889634f;
constexpr unsigned SPIN_LIMIT = 1u << 22;

constexpr int SM_SLOT  = 0;
constexpr int SM_QA    = 196608;
constexpr int SM_P     = SM_QA + 16384;
constexpr int SM_RED1  = SM_P + 4096;
constexpr int SM_RED2  = SM_RED1 + 2048;
constexpr int SM_VEC   = SM_RED2 + 4096;
constexpr int SM_BAR   = SM_VEC + 3072;
constexpr int SM_TOTAL = SM_BAR + 352;
constexpr int V_X    = 512;
constexpr int BAR_FULL = 0;
constexpr int BAR_PDONE= 48;
constexpr int BAR_BDONE= 56;
constexpr int BAR_QABS = 72;
constexpr int BAR_BFULL= 80;
constexpr int BAR_BEMPTY=120;
constexpr int BAR_WFREE= 160;
constexpr int BAR_W    = 168;
constexpr int BAR_S    = 192;
constexpr int BAR_Q    = 264;
constexpr int W_EPOCH  = 328;
constexpr int W_PROG   = 336;
constexpr int SM_WQ = 3 * 32768, SM_WQB = 4 * 32768, SM_WUK = 5 * 32768;
constexpr int SM_SQ = 3 * 32768;
constexpr int XSTR = 1024 + 16;

struct __align__(128) Cnt { unsigned v; unsigned pad[31]; };
struct __align__(128) Scratch {
    Cnt epoch, ticket, cntQabs, cntB;
    float qA[64 * 128], qB[64 * 128];
    __nv_bfloat16 qabs[2 * 32 * 512];
    float  partO[NT * 128];
    float2 partML[NT * 4];
    float  bpart[NB_CTA * 32 * 512];
    float2 bml[NB_CTA * 32];
    float  ctx[32 * 4 * 2 * 128];
    float  o[2 * 4096];
    Cnt    clk;
};
__device__ __align__(128) unsigned char g_raw[sizeof(Scratch)];

__device__ __forceinline__ int slice_of(int cta) {
    return cta >= 128 ? cta : ((cta & 8) << 3) | ((cta >> 4) << 3) | (cta & 7);
}

#define STAMP(cond, i) do {} while (0)
#define LAND(cond, i) do {} while (0)

__device__ __forceinline__ void mbar_init(uint32_t bar, int cnt) {
    asm volatile("mbarrier.init.shared::cta.b64 [%0], %1;" ::"r"(bar), "r"(cnt) : "memory");
}
__device__ __forceinline__ void mbar_expect_tx(uint32_t bar, uint32_t bytes) {
    asm volatile("mbarrier.arrive.expect_tx.shared::cta.b64 _, [%0], %1;" ::"r"(bar), "r"(bytes) : "memory");
}
__device__ __forceinline__ void mbar_arrive(uint32_t bar) {
    asm volatile("mbarrier.arrive.shared::cta.b64 _, [%0];" ::"r"(bar) : "memory");
}
__device__ __forceinline__ void mbar_wait(uint32_t bar, uint32_t parity) {
    unsigned it = 0;
    while (true) {
        uint32_t ok;
        asm volatile("{\n.reg .pred p;\nmbarrier.try_wait.parity.shared::cta.b64 p, [%1], %2;\nselp.u32 %0, 1, 0, p;\n}\n"
                     : "=r"(ok) : "r"(bar), "r"(parity) : "memory");
        if (ok) break;
        if (++it > SPIN_LIMIT) __trap();
    }
}
__device__ __forceinline__ void mbar_wait_nt(uint32_t bar, uint32_t parity) {
#pragma unroll 1
    for (unsigned it = 0; it < SPIN_LIMIT; it++) {
        uint32_t ok;
        asm volatile("{\n.reg .pred p;\nmbarrier.try_wait.parity.shared::cta.b64 p, [%1], %2;\nselp.u32 %0, 1, 0, p;\n}\n"
                     : "=r"(ok) : "r"(bar), "r"(parity) : "memory");
        if (ok) break;
    }
}
__device__ __forceinline__ bool mbar_test(uint32_t bar, uint32_t parity) {
    uint32_t ok;
    asm volatile("{\n.reg .pred p;\nmbarrier.test_wait.parity.shared::cta.b64 p, [%1], %2;\nselp.u32 %0, 1, 0, p;\n}\n"
                 : "=r"(ok) : "r"(bar), "r"(parity) : "memory");
    return ok;
}
__device__ __forceinline__ void bulk_load(uint32_t dst, const void* src, uint32_t bytes, uint32_t bar, uint64_t pol) {
    asm volatile("cp.async.bulk.shared::cluster.global.mbarrier::complete_tx::bytes.L2::cache_hint [%0], [%1], %2, [%3], %4;"
                 ::"r"(dst), "l"(src), "r"(bytes), "r"(bar), "l"(pol) : "memory");
}
__device__ __forceinline__ void bulk_load_nohint(uint32_t dst, const void* src, uint32_t bytes, uint32_t bar) {
    asm volatile("cp.async.bulk.shared::cluster.global.mbarrier::complete_tx::bytes [%0], [%1], %2, [%3];"
                 ::"r"(dst), "l"(src), "r"(bytes), "r"(bar) : "memory");
}
__device__ __forceinline__ void tma_2d(uint32_t dst, const CUtensorMap* map, int c0, int c1, uint32_t bar, uint64_t pol) {
    asm volatile("cp.async.bulk.tensor.2d.shared::cluster.global.mbarrier::complete_tx::bytes.L2::cache_hint [%0], [%1, {%3, %4}], [%2], %5;"
                 ::"r"(dst), "l"(map), "r"(bar), "r"(c0), "r"(c1), "l"(pol) : "memory");
}
__device__ __forceinline__ void tma_3d(uint32_t dst, const CUtensorMap* map, int c1, int c2, uint32_t bar, uint64_t pol) {
    asm volatile("cp.async.bulk.tensor.3d.shared::cluster.global.mbarrier::complete_tx::bytes.L2::cache_hint [%0], [%1, {%3, %4, %5}], [%2], %6;"
                 ::"r"(dst), "l"(map), "r"(bar), "r"(0), "r"(c1), "r"(c2), "l"(pol) : "memory");
}
__device__ __forceinline__ void wait_prog(const unsigned char* smem_word, unsigned th) {
    unsigned it = 0;
    while (*(volatile const unsigned*)(smem_word + 8) + NSTATIC < th) {
        __nanosleep(SLP);
        if (++it > SPIN_LIMIT) __trap();
    }
}
__device__ __forceinline__ uint32_t now_ns() {
    uint32_t t;
    asm volatile("mov.u32 %0, %globaltimer_lo;" : "=r"(t) :: "memory");
    return t;
}
__device__ __forceinline__ void note_draw(unsigned char* smem_word, unsigned raw, unsigned* clk, uint32_t tag) {
    const uint32_t a = (uint32_t)__cvta_generic_to_shared(smem_word);
    asm volatile("st.volatile.u32 [%0], %1;" ::"l"(smem_word + 8), "r"(raw) : "memory");
    const uint32_t now = now_ns();
    if ((int)raw < NT - NSTATIC - FRZ) asm volatile("st.volatile.shared.v2.u32 [%0], {%1, %2};" ::"r"(a), "r"(raw), "r"(now) : "memory");
    const unsigned q = NT - NSTATIC - FRZ - raw;
    if ((q & ~((GN - 1) * GST)) == 0)
        asm volatile("st.relaxed.gpu.global.u32 [%0], %1;" ::"l"(clk + q / GST), "r"(((now + q * 10) & ~1u) | tag) : "memory");
}
template <int SLEEP = SLT>
__device__ __forceinline__ void wait_ticket(const unsigned char* smem_word, int th) {
    wait_prog(smem_word, min(th, NT - NEARX));
    uint32_t tk, t0;
#pragma unroll 1
    for (unsigned it = 0; it < SPIN_LIMIT; it++) {
        asm volatile("ld.volatile.shared.v2.u32 {%0, %1}, [%2];" : "=r"(tk), "=r"(t0) : "r"((uint32_t)__cvta_generic_to_shared(smem_word)) : "memory");
        if ((int)(now_ns() - t0) >= (th - NSTATIC - (int)tk) * 10) break;
        if (SLEEP) __nanosleep(SLEEP);
    }
}
__device__ __forceinline__ bool mbar_wait_for(uint32_t bar, uint32_t parity, int n) {
    uint32_t c0, c;
    asm volatile("mov.u32 %0, %%clock;" : "=r"(c0) :: "memory");
    do {
        if (mbar_test(bar, parity)) return true;
        asm volatile("mov.u32 %0, %%clock;" : "=r"(c) :: "memory");
    } while ((int)(c - c0) < n);
    return false;
}
__device__ __forceinline__ bool elect_one() {
    uint32_t p;
    asm volatile("{\n.reg .pred p;\nelect.sync _|p, 0xffffffff;\nselp.u32 %0, 1, 0, p;\n}\n" : "=r"(p));
    return p;
}
__device__ __forceinline__ void fence_proxy_async() { asm volatile("fence.proxy.async;" ::: "memory"); }
__device__ __forceinline__ void named_bar(int id, int n) { asm volatile("bar.sync %0, %1;" ::"r"(id), "r"(n) : "memory"); }

__device__ __forceinline__ uint4 lds128(uint32_t a) {
    uint4 v;
    asm volatile("ld.shared.v4.u32 {%0,%1,%2,%3}, [%4];" : "=r"(v.x), "=r"(v.y), "=r"(v.z), "=r"(v.w) : "r"(a));
    return v;
}
__device__ __forceinline__ uint4 ldsm4(uint32_t a) {
    uint4 v;
    asm volatile("ldmatrix.sync.aligned.m8n8.x4.shared.b16 {%0,%1,%2,%3}, [%4];" : "=r"(v.x), "=r"(v.y), "=r"(v.z), "=r"(v.w) : "r"(a));
    return v;
}
__device__ __forceinline__ uint4 ldsm4t(uint32_t a) {
    uint4 v;
    asm volatile("ldmatrix.sync.aligned.m8n8.x4.trans.shared.b16 {%0,%1,%2,%3}, [%4];" : "=r"(v.x), "=r"(v.y), "=r"(v.z), "=r"(v.w) : "r"(a));
    return v;
}
__device__ __forceinline__ uint2 lds64(uint32_t a) {
    uint2 v;
    asm volatile("ld.shared.v2.u32 {%0,%1}, [%2];" : "=r"(v.x), "=r"(v.y) : "r"(a));
    return v;
}
__device__ __forceinline__ uint4 ld_relaxed128(const void* p) {
    uint4 v;
    asm volatile("ld.relaxed.gpu.global.v4.u32 {%0,%1,%2,%3}, [%4];" : "=r"(v.x), "=r"(v.y), "=r"(v.z), "=r"(v.w) : "l"(p) : "memory");
    return v;
}
__device__ __forceinline__ uint2 ld_relaxed64(const void* p) {
    uint2 v;
    asm volatile("ld.relaxed.gpu.global.v2.u32 {%0,%1}, [%2];" : "=r"(v.x), "=r"(v.y) : "l"(p) : "memory");
    return v;
}
__device__ __forceinline__ uint32_t ld_relaxed32(const void* p) {
    uint32_t v;
    asm volatile("ld.relaxed.gpu.global.u32 %0, [%1];" : "=r"(v) : "l"(p) : "memory");
    return v;
}
__device__ __forceinline__ uint32_t ld_acquire32(const void* p) {
    uint32_t v;
    asm volatile("ld.acquire.gpu.global.u32 %0, [%1];" : "=r"(v) : "l"(p) : "memory");
    return v;
}
__device__ __forceinline__ void st_relaxed128(void* p, uint32_t a, uint32_t b, uint32_t c, uint32_t d) {
    asm volatile("st.relaxed.gpu.global.v4.u32 [%0], {%1,%2,%3,%4};" ::"l"(p), "r"(a), "r"(b), "r"(c), "r"(d) : "memory");
}
__device__ __forceinline__ void red_release(unsigned* p) {
    asm volatile("red.release.gpu.global.add.u32 [%0], 1;" ::"l"(p) : "memory");
}
__device__ __forceinline__ void wait_counter(const unsigned* p, unsigned target, unsigned ns) {
    unsigned it = 0;
    while ((int)(ld_acquire32(p) - target) < 0) {
        __nanosleep(ns);
        if (++it > SPIN_LIMIT) __trap();
    }
}
__device__ __forceinline__ uint32_t prmt(uint32_t a, uint32_t b, uint32_t s) {
    uint32_t d;
    asm("prmt.b32 %0, %1, %2, %3;" : "=r"(d) : "r"(a), "r"(b), "r"(s));
    return d;
}
__device__ __forceinline__ uint32_t pack_bf16(float lo, float hi) {
    uint32_t d;
    asm("cvt.rn.bf16x2.f32 %0, %1, %2;" : "=r"(d) : "f"(hi), "f"(lo));
    return d;
}
__device__ __forceinline__ float ex2(float x) {
    float y;
    asm("ex2.approx.ftz.f32 %0, %1;" : "=f"(y) : "f"(x));
    return y;
}
__device__ __forceinline__ float bf_lo(uint32_t v) { return __uint_as_float(v << 16); }
__device__ __forceinline__ float bf_hi(uint32_t v) { return __uint_as_float(v & 0xffff0000u); }
__device__ __forceinline__ void scale_scores(float& a, float& b) {
    uint32_t p = pack_bf16(a, b);
    p = pack_bf16(bf_lo(p) * SCALE, bf_hi(p) * SCALE);
    a = bf_lo(p); b = bf_hi(p);
}
__device__ __forceinline__ uint32_t tagw(float v, uint32_t tag) {
    uint32_t d;
    asm("lop3.b32 %0, %1, 0xfffffffe, %2, 0xEA;" : "=r"(d) : "r"(__float_as_uint(v)), "r"(tag));
    return d;
}
__device__ __forceinline__ uint32_t bad2(uint32_t x, uint32_t y, uint32_t tag) {
    uint32_t d;
    asm("lop3.b32 %0, %1, %2, %3, 0x7E;" : "=r"(d) : "r"(x), "r"(y), "r"(tag));
    return d;
}
__device__ __forceinline__ uint32_t bad4(const uint4& v, uint32_t tag) { return bad2(v.x, v.y, tag) | bad2(v.z, v.w, tag); }
__device__ __forceinline__ void ld_relaxed128_if(uint4& v, const void* p, uint32_t c) {
    asm volatile("{\n.reg .pred p;\nsetp.ne.u32 p, %5, 0;\n@p ld.relaxed.gpu.global.v4.u32 {%0,%1,%2,%3}, [%4];\n}\n"
                 : "+r"(v.x), "+r"(v.y), "+r"(v.z), "+r"(v.w) : "l"(p), "r"(c) : "memory");
}
__device__ __forceinline__ void ld_relaxed64_if(uint2& v, const void* p, uint32_t c) {
    asm volatile("{\n.reg .pred p;\nsetp.ne.u32 p, %3, 0;\n@p ld.relaxed.gpu.global.v2.u32 {%0,%1}, [%2];\n}\n"
                 : "+r"(v.x), "+r"(v.y) : "l"(p), "r"(c) : "memory");
}
__device__ __forceinline__ void st_relaxed32(void* p, uint32_t a) {
    asm volatile("st.relaxed.gpu.global.u32 [%0], %1;" ::"l"(p), "r"(a) : "memory");
}
__device__ __forceinline__ void red_out(uint32_t* word, float v, int col, uint32_t go) {
    const uint32_t pk = (col & 1) ? pack_bf16(-0.f, v) : pack_bf16(v, -0.f);
    asm volatile("{\n.reg .pred p;\nsetp.ne.u32 p, %2, 0;\n@p red.relaxed.gpu.global.add.noftz.bf16x2 [%0], %1;\n}\n"
                 ::"l"(word), "r"(pk), "r"(go) : "memory");
}
__device__ __forceinline__ void mma16816(float (&c)[4], uint32_t a0, uint32_t a1, uint32_t a2, uint32_t a3,
                                         uint32_t b0, uint32_t b1) {
    asm("mma.sync.aligned.m16n8k16.row.col.f32.bf16.bf16.f32 {%0,%1,%2,%3}, {%4,%5,%6,%7}, {%8,%9}, {%0,%1,%2,%3};"
        : "+f"(c[0]), "+f"(c[1]), "+f"(c[2]), "+f"(c[3])
        : "r"(a0), "r"(a1), "r"(a2), "r"(a3), "r"(b0), "r"(b1));
}
__device__ __forceinline__ uint64_t make_desc(uint32_t addr) {
    return (uint64_t)((addr & 0x3FFFF) >> 4) | ((uint64_t)1 << 16) | ((uint64_t)64 << 32) | ((uint64_t)1 << 62);
}
template <int TRANS_A>
__device__ __forceinline__ void wgmma_n32(float (&d)[16], uint64_t da, uint64_t db, int scale_d) {
    asm volatile("{\n.reg .pred p;\nsetp.ne.b32 p, %18, 0;\n"
                 "wgmma.mma_async.sync.aligned.m64n32k16.f32.bf16.bf16 "
                 "{%0,%1,%2,%3,%4,%5,%6,%7,%8,%9,%10,%11,%12,%13,%14,%15}, %16, %17, p, 1, 1, %19, 0;\n}\n"
                 : "+f"(d[0]), "+f"(d[1]), "+f"(d[2]), "+f"(d[3]), "+f"(d[4]), "+f"(d[5]), "+f"(d[6]), "+f"(d[7]),
                   "+f"(d[8]), "+f"(d[9]), "+f"(d[10]), "+f"(d[11]), "+f"(d[12]), "+f"(d[13]), "+f"(d[14]), "+f"(d[15])
                 : "l"(da), "l"(db), "r"(scale_d), "n"(TRANS_A));
}
__device__ __forceinline__ void wg_fence()  { asm volatile("wgmma.fence.sync.aligned;" ::: "memory"); }
__device__ __forceinline__ void wg_commit() { asm volatile("wgmma.commit_group.sync.aligned;" ::: "memory"); }
template <int N> __device__ __forceinline__ void wg_wait() { asm volatile("wgmma.wait_group.sync.aligned %0;" ::"n"(N) : "memory"); }

__device__ __forceinline__ void issue_tall(uint32_t dst, const CUtensorMap* map, int col, int row, uint32_t bar, uint64_t pol) {
    tma_2d(dst, map, col, row, bar, pol);
    tma_2d(dst + 16384, map, col, row + 256, bar, pol);
}
__device__ __forceinline__ void tall_prep(uint2 (&bf)[16], uint32_t xbase, int w4, int g, int t) {
    const uint32_t xp = xbase + ((g >> 1) & 1) * 1024 + w4 * 256 + (t >> 1) * 8;
    const uint32_t sel = (g & 1) ? ((t & 1) ? 0x3244u : 0x1044u) : ((t & 1) ? 0x4432u : 0x4410u);
#pragma unroll
    for (int i = 0; i < 16; i++) {
        const uint2 xw = lds64(xp + i * 16);
        bf[i] = make_uint2(prmt(xw.x, 0, sel), prmt(xw.y, 0, sel));
    }
}
__device__ __forceinline__ void gemv_tall(uint32_t wbase, const uint2 (&bf)[16], float* red, int w4, int g, int t) {
    const uint32_t wu = wbase + (128 * w4 + (t & 1) + 4 * (t >> 1)) * 64 + (((g >> 1) ^ (t & 2)) << 4) + (g & 1) * 8;
    const uint32_t wv = (wu + 128) ^ 16;
    float a[4][4];
#pragma unroll
    for (int i = 0; i < 16; i++) (&a[0][0])[i] = 0.f;
#pragma unroll
    for (int i = 0; i < 16; i++) {
        const uint2 u = lds64(wu + i * 512), v = lds64(wv + i * 512);
        mma16816(a[i & 3], u.x, u.y, v.x, v.y, bf[i].x, bf[i].y);
    }
    if (t < 2)
        *(float4*)(red + (w4 * 2 + t) * 32 + 4 * g) =
            make_float4((a[0][0] + a[1][0]) + (a[2][0] + a[3][0]), (a[0][1] + a[1][1]) + (a[2][1] + a[3][1]),
                        (a[0][2] + a[1][2]) + (a[2][2] + a[3][2]), (a[0][3] + a[1][3]) + (a[2][3] + a[3][3]));
}
__device__ __forceinline__ void tall_finish(const float* red, float* dst, int tid, uint32_t tag, int lo = 0, int hi = 64) {
    named_bar(1, 128);
    if (tid >= lo && tid < hi) {
        st_relaxed32(dst, tagw((red[tid] + red[64 + tid]) + (red[128 + tid] + red[192 + tid]), tag));
    }
}

__device__ __forceinline__ void combineA(Scratch& G, int bh, int dq, uint32_t tag, float* red, int tid, const unsigned char* prog) {
    const int r = tid >> 3, c4 = tid & 7, w4 = tid >> 5, lane = tid & 31;
    const float2* ml = G.partML + (bh * 128 + r) * 4;
    const float* po = G.partO + (size_t)(bh * 128 + r) * 128 + dq * 32 + c4 * 4;
    uint2 m[8];
    uint4 o[8];
    uint32_t bad[8];
    STAMP(tid == 0 && bh >= 32, 28);
#pragma unroll
    for (int k = 0; k < 8; k++) m[k] = ld_relaxed64(ml + 64 * k);
#pragma unroll
    for (int k = 0; k < 8; k++) {
        o[k] = make_uint4(~tag, ~tag, ~tag, ~tag);
        ld_relaxed128_if(o[k], po + (size_t)k * 16 * 128, bh < 60);
    }
    unsigned it = 0;
    while (true) {
        uint32_t any = 0;
#pragma unroll
        for (int k = 0; k < 8; k++) { bad[k] = bad2(m[k].x, m[k].y, tag) & 1u; any |= bad[k]; }
        if (!__any_sync(~0u, any)) break;
#pragma unroll
        for (int k = 0; k < 8; k++) ld_relaxed64_if(m[k], ml + 64 * k, bad[k]);
        if (++it > SPIN_LIMIT) __trap();
    }
    STAMP(tid == 0 && bh >= 32, 30);
    STAMP(tid == 0 && bh >= 32, 19);
    float M = fmaxf(fmaxf(fmaxf(__uint_as_float(m[0].x), __uint_as_float(m[1].x)), fmaxf(__uint_as_float(m[2].x), __uint_as_float(m[3].x))),
                    fmaxf(fmaxf(__uint_as_float(m[4].x), __uint_as_float(m[5].x)), fmaxf(__uint_as_float(m[6].x), __uint_as_float(m[7].x))));
    M = fmaxf(M, __shfl_xor_sync(~0u, M, 8));
    M = fmaxf(M, __shfl_xor_sync(~0u, M, 16));
    float wgt[8], L = 0.f;
#pragma unroll
    for (int k = 0; k < 8; k++) {
        wgt[k] = ex2(__uint_as_float(m[k].x) - M);
        L = fmaf(wgt[k], __uint_as_float(m[k].y), L);
    }
    L += __shfl_xor_sync(~0u, L, 8);
    L += __shfl_xor_sync(~0u, L, 16);
    if (lane == 0) { red[128 + w4] = M; red[132 + w4] = L; }
    named_bar(1, 128);
    {
        const float4 Mw = *(float4*)(red + 128), Lw = *(float4*)(red + 132);
        const float Mx = fmaxf(fmaxf(Mw.x, Mw.y), fmaxf(Mw.z, Mw.w));
        const float Lt = (ex2(Mw.x - Mx) * Lw.x + ex2(Mw.y - Mx) * Lw.y) + (ex2(Mw.z - Mx) * Lw.z + ex2(Mw.w - Mx) * Lw.w);
        const float f = ex2(M - Mx) / Lt;
#pragma unroll
        for (int k = 0; k < 8; k++) wgt[k] *= f;
    }
    STAMP(tid == 0 && bh >= 32, 23);
    if (bh >= 60) wait_ticket(prog, NT + YO + (bh - 63) * YOS);
    while (true) {
        uint32_t any = 0;
#pragma unroll
        for (int k = 0; k < 8; k++) { bad[k] = bad4(o[k], tag) & 1u; any |= bad[k]; }
        if (!__any_sync(~0u, any)) break;
#pragma unroll
        for (int k = 0; k < 8; k++) ld_relaxed128_if(o[k], po + (size_t)k * 16 * 128, bad[k]);
        if (++it > SPIN_LIMIT) __trap();
    }
    STAMP(tid == 0 && bh >= 32, 31);
    float a0 = 0.f, a1 = 0.f, a2 = 0.f, a3 = 0.f, b0 = 0.f, b1 = 0.f, b2 = 0.f, b3 = 0.f;
#pragma unroll
    for (int k = 0; k < 8; k += 2) {
        a0 = fmaf(wgt[k], __uint_as_float(o[k].x), a0); b0 = fmaf(wgt[k + 1], __uint_as_float(o[k + 1].x), b0);
        a1 = fmaf(wgt[k], __uint_as_float(o[k].y), a1); b1 = fmaf(wgt[k + 1], __uint_as_float(o[k + 1].y), b1);
        a2 = fmaf(wgt[k], __uint_as_float(o[k].z), a2); b2 = fmaf(wgt[k + 1], __uint_as_float(o[k + 1].z), b2);
        a3 = fmaf(wgt[k], __uint_as_float(o[k].w), a3); b3 = fmaf(wgt[k + 1], __uint_as_float(o[k + 1].w), b3);
    }
    a0 += b0; a1 += b1; a2 += b2; a3 += b3;
#pragma unroll
    for (int s = 8; s <= 16; s <<= 1) {
        a0 += __shfl_xor_sync(~0u, a0, s);
        a1 += __shfl_xor_sync(~0u, a1, s);
        a2 += __shfl_xor_sync(~0u, a2, s);
        a3 += __shfl_xor_sync(~0u, a3, s);
    }
    if (lane < 8) *(float4*)(red + w4 * 32 + c4 * 4) = make_float4(a0, a1, a2, a3);
    named_bar(1, 128);
    STAMP(tid == 0 && bh >= 32, 24);
}

struct Ptrs {
    const __nv_bfloat16 *K, *xA, *xB;
    __nv_bfloat16* out;
    Scratch* g;
};
struct Maps { CUtensorMap m_wq, m_v, m_ckv, m_wqB, m_wuk, m_uv[2], m_w[2]; };

__global__ void __launch_bounds__(NTHREADS, 1)
fused_decode_kernel(const Ptrs P, const __grid_constant__ Maps M) {
    extern __shared__ __align__(1024) unsigned char smem[];
    const uint32_t sb = (uint32_t)__cvta_generic_to_shared(smem);
    uint64_t pol;
    asm("createpolicy.fractional.L2::evict_first.b64 %0, 1.0;" : "=l"(pol));
    asm volatile("{\n.reg .pred p;\nsetp.lt.u32 p, %3, 32;\n@p cp.async.bulk.prefetch.L2.global.L2::cache_hint [%0], %1, %2;\n}\n"
                 ::"l"((const char*)P.K + (blockIdx.x << 14)), "n"(PFB), "l"(pol), "r"(threadIdx.x) : "memory");
    if (threadIdx.x < 32 && elect_one()) {
        mbar_init(sb + SM_BAR + BAR_FULL, 1);
        mbar_init(sb + SM_BAR + BAR_W, 1);
        asm volatile("fence.mbarrier_init.release.cluster;" ::: "memory");
        if (blockIdx.x < NA_CTA) {
            mbar_expect_tx(sb + SM_BAR + BAR_FULL, 16384);
            bulk_load(sb + SM_SLOT, (const char*)P.K + (blockIdx.x << 14), 16384, sb + SM_BAR + BAR_FULL, pol);
        }
        if (blockIdx.x < 128) {
            mbar_expect_tx(sb + SM_BAR + BAR_W, 32768 + 4096);
            issue_tall(sb + SM_WQ, &M.m_wq, slice_of(blockIdx.x) * 32, 0, sb + SM_BAR + BAR_W, pol);
            bulk_load_nohint(sb + SM_P, P.xA, 2048, sb + SM_BAR + BAR_W);
            bulk_load_nohint(sb + SM_P + 2048, P.xB, 2048, sb + SM_BAR + BAR_W);
        }
    }
    const int tid = threadIdx.x, warp = __shfl_sync(~0u, tid >> 5, 0), lane = tid & 31;
    const int g = lane >> 2, t = lane & 3;
    const int cta = blockIdx.x;
    Scratch& G = *P.g;
    const bool isB = cta >= NA_CTA;
    const bool hasSlice = cta < 128;
    const int j = slice_of(cta), h = j >> 2, qd = cta & 3;
    const int mat = j >> 6, cg = j & 7, rg = (j >> 3) & 7;
    const bool late = j < JE0 || j >= 124;
    STAMP(tid == 32, 0);
    if (warp == 7) {
        __syncthreads();
        const uint32_t epoch = *(volatile uint32_t*)(smem + SM_BAR + W_EPOCH);
        const uint32_t tag = (epoch + 1) & 1;
        if (!isB) { mbar_wait(sb + SM_BAR + BAR_W, 0); __nanosleep(QDELAY); }
#pragma unroll 1
        for (int i = 0; i < 8; i++) {
            if (i == 4 && !isB) wait_prog(smem + SM_BAR + W_PROG, 16 * 128);
            if (i == 0 && isB) { mbar_wait(sb + SM_BAR + BAR_QABS, 0); __nanosleep(8000); }
            uint4 v[8];
            uint32_t bad[8];
#pragma unroll
            for (int k = 0; k < 8; k++) { bad[k] = 1; v[k] = make_uint4(0, 0, 0, 0); }
            unsigned it = 0;
            while (true) {
#pragma unroll
                for (int k = 0; k < 8; k++) ld_relaxed128_if(v[k], G.qA + (8 * i + k) * 128 + lane * 4, bad[k]);
                uint32_t any = 0;
#pragma unroll
                for (int k = 0; k < 8; k++) { bad[k] = bad4(v[k], tag) & 1u; any |= bad[k]; }
                if (!__any_sync(~0u, any)) break;
                __nanosleep(40);
                if (++it > SPIN_LIMIT) __trap();
            }
#pragma unroll
            for (int k = 0; k < 8; k++) {
                uint32_t* dst = (uint32_t*)(smem + SM_QA + (8 * i + k) * 256 + (lane >> 1) * 16 + (lane & 1) * 4);
                dst[0] = pack_bf16(__uint_as_float(v[k].x), __uint_as_float(v[k].y));
                dst[2] = pack_bf16(__uint_as_float(v[k].z), __uint_as_float(v[k].w));
            }
            __syncwarp();
            if (lane == 0) mbar_arrive(sb + SM_BAR + BAR_Q + i * 8);
            STAMP(lane == 0 && i == 0, 2);
        }
        STAMP(lane == 0, 21);
        if (hasSlice) mbar_wait(sb + SM_BAR + BAR_PDONE, 0);
#pragma unroll 1
        for (int p = 0; p < 12; p++) {
            const bool uv = p < 4;
            if (p == (late ? 0 : 4)) {
                wait_ticket(smem + SM_BAR + W_PROG, NT - FRZ + GLOOK);
                uint32_t v;
                unsigned it = 0;
                while (true) {
                    v = ld_relaxed32(&G.clk.v + (lane & (GN - 1)));
                    if (!__any_sync(~0u, (v ^ tag) & 1u)) break;
                    __nanosleep(200);
                    if (++it > SPIN_LIMIT) __trap();
                }
                const uint32_t v0 = __shfl_sync(~0u, v, 0);
                v = v0 + (__reduce_add_sync(~0u, (int)(v - v0)) >> 5);
                if (lane == 0)
                    asm volatile("st.volatile.shared.v2.u32 [%0], {%1, %2};" ::"r"(sb + SM_BAR + W_PROG), "r"(NT - NSTATIC - FRZ), "r"(v) : "memory");
                __syncwarp();
                if (!hasSlice) break;
            }
            if (lane == 0) {
                const int r = uv ? p * 128 : (p - 4) * 64;
                if (!uv || late)
                    wait_ticket<NSL>(smem + SM_BAR + W_PROG, NT + (uv ? YV + (p * DV >> 1) : YW + ((p - 4) * DW >> 1) + (p == 11 ? DL : 0)));
                STAMP(p == 4, 10);
                const uint32_t bar = sb + SM_BAR + BAR_S + (p < 11 ? p >> 1 : 6) * 8;
                if (!(p & 1) || p == 11) mbar_expect_tx(bar, p < 10 ? 16384 : 8192);
                tma_2d(sb + SM_SQ + p * 8192, uv ? &M.m_uv[late] : &M.m_w[mat], uv ? j * 32 : cg * 64,
                       uv ? r : (rg + 8 * (r >> 7)) * 128 + (r & 127), bar, pol);
            }
            __syncwarp();
        }
    } else if (warp >= 4) {
        const int wi = warp - 4;
        const uint32_t slot = sb + SM_SLOT + wi * 32768;
        const uint32_t bar = sb + SM_BAR + BAR_FULL + wi * 16, barV = bar + 8;
        unsigned tk = wi * NA_CTA + cta;
        const int ev = wi;
        if (lane == 0) {
            if (wi) mbar_init(bar, 1);
            mbar_init(barV, 1);
            if (isB && wi == 0) {
                for (int s = 0; s < 5; s++) {
                    mbar_init(sb + SM_BAR + BAR_BFULL + s * 8, 1);
                    mbar_init(sb + SM_BAR + BAR_BEMPTY + s * 8, 4);
                }
            }
            asm volatile("fence.mbarrier_init.release.cluster;" ::: "memory");
        }
        __syncthreads();
        const uint32_t epoch = *(volatile uint32_t*)(smem + SM_BAR + W_EPOCH);
        const uint32_t tag = (epoch + 1) & 1;

        bool active = true;
        if (isB) {
            if (wi == 1 && lane == 0) {
                wait_counter(&G.cntQabs.v, (epoch + 1) * 128, 64);
                fence_proxy_async();
                mbar_expect_tx(sb + SM_BAR + BAR_QABS, 32768);
                bulk_load_nohint(sb + SM_SLOT + 5 * 32768, G.qabs + ((cta - NA_CTA) >> 3) * 16384, 32768, sb + SM_BAR + BAR_QABS);
            }
            if (wi == 0 && lane == 0) {
                const int ib = cta - NA_CTA;
                int s = 0, sl = 0; uint32_t ph = 1, phl = 0;
                for (int u = 0; u < 32; u++) {
                    if (u >= BINFL) {
                        mbar_wait(sb + SM_BAR + BAR_BFULL + sl * 8, phl);
                        LAND(true, 16384 + ib * 32 + u);
                        if (++sl == 5) { sl = 0; phl ^= 1; }
                    }
                    if (u == 3 && hasSlice) mbar_wait(sb + SM_BAR + BAR_WFREE, 0);
                    mbar_wait(sb + SM_BAR + BAR_BEMPTY + s * 8, ph);
                    const uint32_t fb = sb + SM_BAR + BAR_BFULL + s * 8;
                    const int row = (ib >> 3) * 8192 + ((u >> 1) * 8 + (ib & 7)) * 64;
                    mbar_expect_tx(fb, 32768);
                    for (int x = 0; x < 4; x++)
                        tma_2d(sb + SM_SLOT + s * 32768 + x * 8192, &M.m_ckv, ((u & 1) * 4 + x) * 64, row, fb, pol);
                    if (++s == 5) { s = 0; ph ^= 1; }
                }
            }
            __syncwarp();
            mbar_wait(sb + SM_BAR + BAR_BDONE, 0);
            if (lane == 0) {
                tk = atomicInc(&G.ticket.v, DRAWS - 1);
                note_draw(smem + SM_BAR + W_PROG, tk, &G.clk.v, tag);
                tk += NSTATIC;
            }
            tk = __shfl_sync(~0u, tk, 0);
            active = tk < NT;
        } else if (ev != 0) {
            __syncwarp();
            mbar_wait(sb + SM_BAR + BAR_W + (ev - 1) * 8, 0);
        }
        if (active) {
            if ((isB || ev != 0) && lane == 0) {
                mbar_expect_tx(bar, 16384);
                bulk_load(slot, (const char*)P.K + (size_t)tk * 16384, 16384, bar, pol);
            }
            const uint32_t kA = slot + g * 256 + t * 16 + (g & 1) * 64, kB = kA ^ 64;
            const uint32_t qo = t * 16 + ((g >> 1) & 1) * 64 + (g & 1) * 8;
            const uint32_t v0 = slot + 16384 + (2 * t) * 128 + ((g ^ (2 * t)) << 4), v1 = (v0 + 128) ^ 16;
            const uint32_t sl0 = (g & 1) ? 0x1044u : 0x4410u, sl1 = (g & 1) ? 0x3244u : 0x4432u;
            const uint32_t sa0 = (g & 2) ? 0x4444u : sl0, sa1 = (g & 2) ? 0x4444u : sl1;
            const uint32_t sb0 = (g & 2) ? sl0 : 0x4444u, sb1 = (g & 2) ? sl1 : 0x4444u;
            const int d0 = 64 * (t >> 1) + 8 * g + 4 * (t & 1);
            uint32_t ph = 0;
            while (true) {
                const uint32_t qa = sb + SM_QA + (tk >> 7) * 256 + qo;
                bool vout = false;
                if (XRV && lane == 0 && tk >= NT - XRV && !mbar_wait_for(bar, ph, TV)) {
                    mbar_expect_tx(barV, 16384);
                    tma_3d(slot + 16384, &M.m_v, tk * 64, 0, barV, pol);
                    vout = true;
                }
                if (XRV) __syncwarp();
                mbar_wait(bar, ph);
                LAND(lane == 0, tk);
                unsigned nxt = 0;
                if (lane == 0) {
                    if (!vout) {
                        mbar_expect_tx(barV, 16384);
                        tma_3d(slot + 16384, &M.m_v, tk * 64, 0, barV, pol);
                    }
                    asm volatile("atom.relaxed.gpu.global.inc.u32 %0, [%1], %2;" : "=r"(nxt) : "l"(&G.ticket.v), "r"(DRAWS - 1) : "memory");
                }
                __syncwarp();
                mbar_wait(sb + SM_BAR + BAR_Q + (tk >> 10) * 8, 0);
                STAMP(tid == 128 && tk < NSTATIC, 3);
                uint2 qf[4];
                qf[0] = lds64(qa); qf[1] = lds64(qa ^ 64); qf[2] = lds64(qa + 128); qf[3] = lds64((qa ^ 64) + 128);
                float c[8][4];
#pragma unroll
                for (int i = 0; i < 32; i++) (&c[0][0])[i] = 0.f;
#pragma unroll
                for (int s = 0; s < 4; s++)
#pragma unroll
                    for (int jj = 0; jj < 8; jj++) {
                        const uint4 u = lds128(((s & 1) ? kB : kA) + jj * 2048 + (s >> 1) * 128);
                        mma16816(c[jj], u.x, u.y, u.z, u.w, qf[s].x, qf[s].y);
                    }
                float sc[8];
#pragma unroll
                for (int jj = 0; jj < 8; jj++) sc[jj] = c[jj][0] + c[jj][3];
#pragma unroll
                for (int jj = 0; jj < 8; jj += 2) scale_scores(sc[jj], sc[jj + 1]);
                float m = fmaxf(fmaxf(fmaxf(sc[0], sc[1]), fmaxf(sc[2], sc[3])), fmaxf(fmaxf(sc[4], sc[5]), fmaxf(sc[6], sc[7])));
                m = fmaxf(m, __shfl_xor_sync(~0u, m, 5));
                m = fmaxf(m, __shfl_xor_sync(~0u, m, 8));
                m = fmaxf(m, __shfl_xor_sync(~0u, m, 16));
                const float ms = __uint_as_float(tagw(m * LOG2E, tag));
                uint32_t W0[4], W1[4];
                float l = 0.f;
#pragma unroll
                for (int i = 0; i < 4; i++) {
                    const uint32_t pp = pack_bf16(ex2(fmaf(sc[2 * i], LOG2E, -ms)), ex2(fmaf(sc[2 * i + 1], LOG2E, -ms)));
                    W0[i] = __shfl_sync(~0u, pp, 8 * t);
                    W1[i] = __shfl_sync(~0u, pp, 8 * t + 5);
                    l += bf_lo(pp) + bf_hi(pp);
                }
                l += __shfl_xor_sync(~0u, l, 5);
                l += __shfl_xor_sync(~0u, l, 8);
                l += __shfl_xor_sync(~0u, l, 16);
                if (lane == 0 || lane == 2)
                    st_relaxed128((char*)G.partML + tk * 32 + lane * 8, __float_as_uint(ms), tagw(l, tag), __float_as_uint(ms), tagw(l, tag));
                uint32_t pb[16][2];
#pragma unroll
                for (int i = 0; i < 16; i++) {
                    const uint32_t pw = (i & 1) ? W1[i >> 2] : W0[i >> 2];
                    pb[i][0] = prmt(pw, 0, (i & 2) ? sa1 : sa0);
                    pb[i][1] = prmt(pw, 0, (i & 2) ? sb1 : sb0);
                    asm volatile("" : "+r"(pb[i][0]), "+r"(pb[i][1]));
                }
                float* po = G.partO + (size_t)tk * 128 + d0;
                asm volatile("" : "+l"(po));
                if (lane == 0) note_draw(smem + SM_BAR + W_PROG, nxt, &G.clk.v, tag);
                nxt += NSTATIC;
                if (nxt >= NT - XPK && nxt < NT && lane == 0) {
                    mbar_expect_tx(bar, 16384);
                    bulk_load(slot, (const char*)P.K + (size_t)nxt * 16384, 16384, bar, pol);
                }
                mbar_wait(barV, ph);
                LAND(lane == 0, 8192 + tk);
                ph ^= 1;
                if (nxt < NT - XPK && lane == 0) {
                    mbar_expect_tx(bar, 16384);
                    bulk_load(slot, (const char*)P.K + (size_t)nxt * 16384, 16384, bar, pol);
                }
                __syncwarp();
                float acc[2][4][4];
#pragma unroll
                for (int i = 0; i < 32; i++) (&acc[0][0][0])[i] = 0.f;
#pragma unroll
                for (int jj = 0; jj < 8; jj++)
#pragma unroll
                    for (int e = 0; e < 2; e++)
#pragma unroll
                        for (int hh = 0; hh < 2; hh++) {
                            const uint4 u = lds128((e ? v1 : v0) + jj * 1024 + hh * 8192);
                            mma16816(acc[hh][(jj & 1) * 2 + e], u.x, u.y, u.z, u.w, pb[2 * jj + e][0], pb[2 * jj + e][1]);
                        }
                float r4[4];
#pragma unroll
                for (int i = 0; i < 4; i++) {
                    const float x0 = (acc[0][0][i] + acc[0][1][i]) + (acc[0][2][i] + acc[0][3][i]);
                    const float x1 = (acc[1][0][i] + acc[1][1][i]) + (acc[1][2][i] + acc[1][3][i]);
                    r4[i] = (t & 2) ? x1 : x0;
                }
                st_relaxed128(po, tagw(r4[0], tag), tagw(r4[1], tag), tagw(r4[2], tag), tagw(r4[3], tag));
                nxt = __shfl_sync(~0u, nxt, 0);
                if (nxt >= NT) break;
                tk = nxt;
            }
            STAMP(lane == 0, 16 + wi);
        }
    } else {
        float* red = (float*)(smem + SM_RED2);
        if (tid == 32) {
            const uint32_t ep0 = ld_relaxed32(&G.epoch.v);
            for (int e = 0; e < 8; e++) mbar_init(sb + SM_BAR + BAR_Q + e * 8, 1);
            for (int e = 1; e < 10; e++) mbar_init(sb + SM_BAR + BAR_W + e * 8, 1);
            mbar_init(sb + SM_BAR + BAR_BDONE, 1);
            mbar_init(sb + SM_BAR + BAR_PDONE, 1);
            mbar_init(sb + SM_BAR + BAR_QABS, 1);
            mbar_init(sb + SM_BAR + BAR_WFREE, 1);
            asm volatile("fence.mbarrier_init.release.cluster;" ::: "memory");
            asm volatile("st.volatile.shared.v4.u32 [%0], {%1, %2, %1, %1};" ::"r"(sb + SM_BAR + W_PROG), "r"(0), "r"(now_ns()) : "memory");
            *(volatile uint32_t*)(smem + SM_BAR + W_EPOCH) = ep0;
        } else if (tid == 64) {
            asm volatile("prefetch.tensormap [%0];" ::"l"(&M.m_v) : "memory");
            asm volatile("prefetch.tensormap [%0];" ::"l"(&M.m_wqB) : "memory");
            asm volatile("prefetch.tensormap [%0];" ::"l"(&M.m_wuk) : "memory");
        }
        __syncthreads();
        const uint32_t epoch = *(volatile uint32_t*)(smem + SM_BAR + W_EPOCH);
        const uint32_t tag = (epoch + 1) & 1;
        STAMP(tid == 0, 14);

        if (hasSlice) {
            const uint32_t nt = tag ^ 1;
            const int qoff = ((tid >> 5) & 1) * 4096 + 32 * j + (tid & 31);
            if (tid < 64) {
                st_relaxed32(G.qA + qoff, nt); st_relaxed32(G.qB + qoff, nt);
                if (tid < 32) {
                    st_relaxed32(G.o + 32 * j + tid, nt); st_relaxed32(G.o + 4096 + 32 * j + tid, nt);
                    st_relaxed32(G.ctx + 32 * j + tid, nt); st_relaxed32(G.ctx + 4096 + 32 * j + tid, nt);
                }
            }
            if (j == 0 && tid >= 96) st_relaxed32(&G.clk.v + lane, nt);
            if (tid >= 64 && tid < 72) st_relaxed32((uint32_t*)P.out + 8 * j + (tid - 64), 0);
            mbar_wait(sb + SM_BAR + BAR_W, 0);
            LAND(tid == 0, 17408 + 0 * 128 + j);
            if (tid == 96) {
                mbar_expect_tx(sb + SM_BAR + BAR_W + 8, 32768);
                issue_tall(sb + SM_WQB, &M.m_wqB, j * 32, 0, sb + SM_BAR + BAR_W + 8, pol);
            }
            __syncwarp();
            STAMP(tid == 0, 15);
            uint2 bf[16];
            tall_prep(bf, sb + SM_P, warp, g, t);
            gemv_tall(sb + SM_WQ, bf, (float*)(smem + SM_RED1), warp, g, t);
            tall_finish((float*)(smem + SM_RED1), G.qA + qoff, tid, tag, 0, h >= HCLR ? 32 : 64);
            STAMP(tid == 0, 1);
            tall_prep(bf, sb + SM_P + 2048, warp, g, t);
            mbar_wait(sb + SM_BAR + BAR_W + 8, 0);
            LAND(tid == 0, 17408 + 1 * 128 + j);
            if (tid == 96) {
                mbar_expect_tx(sb + SM_BAR + BAR_W + 16, 32768);
                tma_2d(sb + SM_WUK, &M.m_wuk, h * 128, qd * 128, sb + SM_BAR + BAR_W + 16, pol);
            }
            __syncwarp();
            gemv_tall(sb + SM_WQB, bf, red, warp, g, t);
            tall_finish(red, G.qB + qoff, tid, tag);
            if (tid == 96) mbar_arrive(sb + SM_BAR + BAR_WFREE);
            STAMP(tid == 0, 25);
            named_bar(1, 128);
            uint4 qf[4];
            {
                const float* qp = G.qB + ((g & 1) * 32 + h) * 128 + t * 8;
                uint4 v[8];
                unsigned it = 0;
                while (true) {
                    uint32_t bad = 0;
#pragma unroll
                    for (int i = 0; i < 8; i++) v[i] = ld_relaxed128(qp + (i >> 1) * 32 + (i & 1) * 4);
#pragma unroll
                    for (int i = 0; i < 8; i++) bad |= bad4(v[i], tag);
                    if (!__any_sync(~0u, bad & 1u)) break;
                    __nanosleep(100);
                    if (++it > SPIN_LIMIT) __trap();
                }
#pragma unroll
                for (int s = 0; s < 4; s++)
                    qf[s] = make_uint4(pack_bf16(__uint_as_float(v[2 * s].x), __uint_as_float(v[2 * s].y)),
                                       pack_bf16(__uint_as_float(v[2 * s].z), __uint_as_float(v[2 * s].w)),
                                       pack_bf16(__uint_as_float(v[2 * s + 1].x), __uint_as_float(v[2 * s + 1].y)),
                                       pack_bf16(__uint_as_float(v[2 * s + 1].z), __uint_as_float(v[2 * s + 1].w)));
            }
            mbar_wait(sb + SM_BAR + BAR_W + 16, 0);
            LAND(tid == 0, 17408 + 2 * 128 + j);
#pragma unroll
            for (int jj = 0; jj < 2; jj++) {
                float c[4] = {0.f, 0.f, 0.f, 0.f};
#pragma unroll
                for (int s = 0; s < 4; s++) {
                    const uint32_t a = sb + SM_WUK + (32 * warp + 16 * jj + g) * 256 + (t + 4 * s) * 16;
                    const uint4 u = lds128(a), v = lds128(a + 2048);
                    mma16816(c, u.x, v.x, u.y, v.y, qf[s].x, qf[s].y);
                    mma16816(c, u.z, v.z, u.w, v.w, qf[s].z, qf[s].w);
                }
                const float val = (t & 2) ? ((t & 1) ? c[3] : c[2]) : ((t & 1) ? c[1] : c[0]);
                const int cc = 128 * qd + 32 * warp + 16 * jj + g + ((t & 2) ? 8 : 0);
                const int off = (cc >> 6) * 2048 + h * 64 + ((((cc & 63) >> 3) ^ (h & 7)) << 3) + (cc & 7);
                G.qabs[(t & 1) * 16384 + off] = __float2bfloat16(val);
            }
            named_bar(1, 128);
            if (tid == 0) red_release(&G.cntQabs.v);
            STAMP(tid == 0, 4);
            if (h >= HCLR) {
#pragma unroll
                for (int k = 0; k < 8; k++)
                    st_relaxed128(G.partO + (size_t)((32 + h) * 128 + 16 * k + (tid >> 3)) * 128 + qd * 32 + (tid & 7) * 4, nt, nt, nt, nt);
                if (tid < 64) st_relaxed128((char*)G.partML + ((32 + h) * 128 + qd * 32) * 32 + tid * 16, nt, nt, nt, nt);
                __threadfence();
                tall_finish((float*)(smem + SM_RED1), G.qA + qoff, tid, tag, 32, 64);
            }
        }

        if (isB) {
            const int ib = cta - NA_CTA;
            float acc[8][16];
#pragma unroll
            for (int i = 0; i < 8; i++)
#pragma unroll
                for (int k = 0; k < 16; k++) acc[i][k] = 0.f;
            float mrun[8], lrun[8];
#pragma unroll
            for (int i = 0; i < 8; i++) { mrun[i] = -INFINITY; lrun[i] = 0.f; }
            const uint64_t dQ = make_desc(sb + SM_SLOT + 5 * 32768);
            const uint64_t dP = make_desc(sb + SM_P);
            const uint32_t pst = sb + SM_P + (((lane >> 4) * 8 + (lane & 7)) * 128) + (((2 * warp + ((lane >> 3) & 1)) ^ (lane & 7)) << 4);
            mbar_wait(sb + SM_BAR + BAR_QABS, 0);
            STAMP(tid == 0, 5);
            int s0 = 0; uint32_t ph0 = 0;
            for (int it = 0; it < 16; it++) {
                int s1 = s0 + 1; uint32_t ph1 = ph0;
                if (s1 == 5) { s1 = 0; ph1 ^= 1; }
                const uint64_t dA0 = make_desc(sb + SM_SLOT + s0 * 32768), dA1 = make_desc(sb + SM_SLOT + s1 * 32768);
                float S[16];
                mbar_wait(sb + SM_BAR + BAR_BFULL + s0 * 8, ph0);
                mbar_wait(sb + SM_BAR + BAR_BFULL + s1 * 8, ph1);
                wg_fence();
#pragma unroll
                for (int k = 0; k < 32; k++) {
                    const uint64_t da = ((k < 16) ? dA0 : dA1) + (uint64_t)((((k >> 2) & 3) * 8192 + (k & 3) * 32) >> 4);
                    const uint64_t db = dQ + (uint64_t)(((k >> 2) * 4096 + (k & 3) * 32) >> 4);
                    wgmma_n32<0>(S, da, db, k > 0);
                }
                wg_commit();
                wg_wait<0>();
#pragma unroll
                for (int i = 0; i < 16; i++) S[i] *= SCALE;
                float mx[8];
#pragma unroll
                for (int i = 0; i < 8; i++) {
                    mx[i] = fmaxf(S[4 * (i >> 1) + (i & 1)], S[4 * (i >> 1) + 2 + (i & 1)]);
                    mx[i] = fmaxf(mx[i], __shfl_xor_sync(~0u, mx[i], 4));
                    mx[i] = fmaxf(mx[i], __shfl_xor_sync(~0u, mx[i], 8));
                    mx[i] = fmaxf(mx[i], __shfl_xor_sync(~0u, mx[i], 16));
                }
                if (g == 0) {
#pragma unroll
                    for (int jb = 0; jb < 4; jb++)
                        *(float2*)(red + warp * 32 + 8 * jb + 2 * t) = make_float2(mx[2 * jb], mx[2 * jb + 1]);
                }
                named_bar(1, 128);
                float al[8];
                bool chg = false;
                uint32_t R[8];
#pragma unroll
                for (int jb = 0; jb < 4; jb++) {
                    float2 a = *(float2*)(red + 8 * jb + 2 * t), b = *(float2*)(red + 32 + 8 * jb + 2 * t);
                    float2 c = *(float2*)(red + 64 + 8 * jb + 2 * t), d = *(float2*)(red + 96 + 8 * jb + 2 * t);
                    const float n0 = fmaxf(mrun[2 * jb], fmaxf(fmaxf(a.x, b.x), fmaxf(c.x, d.x)) * LOG2E);
                    const float n1 = fmaxf(mrun[2 * jb + 1], fmaxf(fmaxf(a.y, b.y), fmaxf(c.y, d.y)) * LOG2E);
                    chg |= (n0 != mrun[2 * jb]) | (n1 != mrun[2 * jb + 1]);
                    al[2 * jb] = ex2(mrun[2 * jb] - n0);
                    al[2 * jb + 1] = ex2(mrun[2 * jb + 1] - n1);
                    mrun[2 * jb] = n0; mrun[2 * jb + 1] = n1;
                    R[2 * jb]     = pack_bf16(ex2(fmaf(S[4 * jb], LOG2E, -n0)), ex2(fmaf(S[4 * jb + 1], LOG2E, -n1)));
                    R[2 * jb + 1] = pack_bf16(ex2(fmaf(S[4 * jb + 2], LOG2E, -n0)), ex2(fmaf(S[4 * jb + 3], LOG2E, -n1)));
                    lrun[2 * jb]     = fmaf(lrun[2 * jb], al[2 * jb], bf_lo(R[2 * jb]) + bf_lo(R[2 * jb + 1]));
                    lrun[2 * jb + 1] = fmaf(lrun[2 * jb + 1], al[2 * jb + 1], bf_hi(R[2 * jb]) + bf_hi(R[2 * jb + 1]));
                }
                asm volatile("stmatrix.sync.aligned.m8n8.x4.trans.shared.b16 [%0], {%1,%2,%3,%4};"
                             ::"r"(pst), "r"(R[0]), "r"(R[1]), "r"(R[2]), "r"(R[3]) : "memory");
                asm volatile("stmatrix.sync.aligned.m8n8.x4.trans.shared.b16 [%0], {%1,%2,%3,%4};"
                             ::"r"(pst + 2048), "r"(R[4]), "r"(R[5]), "r"(R[6]), "r"(R[7]) : "memory");
                asm volatile("fence.proxy.async.shared::cta;" ::: "memory");
                if (__any_sync(~0u, chg)) {
#pragma unroll
                    for (int mt = 0; mt < 8; mt++)
#pragma unroll
                        for (int k = 0; k < 16; k++) acc[mt][k] *= al[2 * (k >> 2) + (k & 1)];
                }
                named_bar(1, 128);
                wg_fence();
#pragma unroll
                for (int mt = 0; mt < 4; mt++)
#pragma unroll
                    for (int kk = 0; kk < 4; kk++)
                        wgmma_n32<1>(acc[mt], dA0 + (uint64_t)((mt * 8192 + kk * 2048) >> 4), dP + (uint64_t)((kk * 32) >> 4), 1);
                wg_commit();
#pragma unroll
                for (int mt = 0; mt < 4; mt++)
#pragma unroll
                    for (int kk = 0; kk < 4; kk++)
                        wgmma_n32<1>(acc[4 + mt], dA1 + (uint64_t)((mt * 8192 + kk * 2048) >> 4), dP + (uint64_t)((kk * 32) >> 4), 1);
                wg_commit();
                wg_wait<1>();
                if (lane == 0) mbar_arrive(sb + SM_BAR + BAR_BEMPTY + s0 * 8);
                wg_wait<0>();
                if (lane == 0) mbar_arrive(sb + SM_BAR + BAR_BEMPTY + s1 * 8);
                s0 = s1 + 1; ph0 = ph1;
                if (s0 == 5) { s0 = 0; ph0 ^= 1; }
            }
#pragma unroll
            for (int i = 0; i < 8; i++) {
                lrun[i] += __shfl_xor_sync(~0u, lrun[i], 4);
                lrun[i] += __shfl_xor_sync(~0u, lrun[i], 8);
                lrun[i] += __shfl_xor_sync(~0u, lrun[i], 16);
            }
            if (g == 0) {
#pragma unroll
                for (int jb = 0; jb < 4; jb++) {
                    *(float2*)(red + 128 + warp * 32 + 8 * jb + 2 * t) = make_float2(lrun[2 * jb], lrun[2 * jb + 1]);
                    if (warp == 0) *(float2*)(red + 256 + 8 * jb + 2 * t) = make_float2(mrun[2 * jb], mrun[2 * jb + 1]);
                }
            }
            named_bar(1, 128);
            if (tid == 0) mbar_arrive(sb + SM_BAR + BAR_BDONE);
            if (tid < 32)
                G.bml[ib * 32 + tid] = make_float2(red[256 + tid], red[128 + tid] + red[160 + tid] + red[192 + tid] + red[224 + tid]);
            float* bp = G.bpart + (size_t)ib * 16384 + (2 * t) * 512 + 16 * warp + g;
#pragma unroll
            for (int mt = 0; mt < 8; mt++)
#pragma unroll
                for (int k = 0; k < 16; k++)
                    bp[(8 * (k >> 2) + (k & 1)) * 512 + 64 * mt + ((k >> 1) & 1) * 8] = acc[mt][k];
            named_bar(1, 128);
            if (tid == 0) red_release(&G.cntB.v);
            STAMP(tid == 0, 6);
        }

        if (hasSlice) {
            if (tid == 0) {
                wait_prog(smem + SM_BAR + W_PROG, TUV);
                wait_counter(&G.cntB.v, (epoch + 1) * NB_CTA, 500);
                if (cta == 0) st_relaxed32(&G.epoch.v, epoch + 1);
                asm volatile("prefetch.tensormap [%0];" ::"l"(&M.m_uv[late]) : "memory");
                asm volatile("prefetch.tensormap [%0];" ::"l"(&M.m_w[mat]) : "memory");
            }
            named_bar(1, 128);
            if (tid == 32) mbar_arrive(sb + SM_BAR + BAR_PDONE);
            STAMP(tid == 0, 7);
            {
                const int b = tid >> 6, cp = tid & 63;
                uint2 ml[8];
#pragma unroll
                for (int i = 0; i < 8; i++) ml[i] = ld_relaxed64(G.bml + (b * 8 + i) * 32 + h);
                uint4 pv[2][8];
#pragma unroll
                for (int i = 0; i < 16; i++)
                    pv[i >> 3][i & 7] = ld_relaxed128(G.bpart + (size_t)(b * 8 + (i & 7)) * 16384 + h * 512 + (i >> 3) * 256 + 4 * cp);
                float M = __uint_as_float(ml[0].x);
#pragma unroll
                for (int i = 1; i < 8; i++) M = fmaxf(M, __uint_as_float(ml[i].x));
                float L = 0.f, wgt[8];
#pragma unroll
                for (int i = 0; i < 8; i++) {
                    wgt[i] = ex2(__uint_as_float(ml[i].x) - M);
                    L = fmaf(wgt[i], __uint_as_float(ml[i].y), L);
                }
                const float inv = 1.f / L;
#pragma unroll
                for (int x = 0; x < 2; x++) {
                    float v0 = 0.f, v1 = 0.f, v2 = 0.f, v3 = 0.f;
#pragma unroll
                    for (int i = 0; i < 8; i++) {
                        v0 = fmaf(wgt[i], __uint_as_float(pv[x][i].x), v0);
                        v1 = fmaf(wgt[i], __uint_as_float(pv[x][i].y), v1);
                        v2 = fmaf(wgt[i], __uint_as_float(pv[x][i].z), v2);
                        v3 = fmaf(wgt[i], __uint_as_float(pv[x][i].w), v3);
                    }
                    *(uint2*)(smem + SM_P + b * 1024 + x * 512 + cp * 8) = make_uint2(pack_bf16(v0 * inv, v1 * inv), pack_bf16(v2 * inv, v3 * inv));
                }
            }
            STAMP(tid == 0, 8);
        }
        {
            named_bar(1, 128);
#pragma unroll 1
            for (uint64_t plan = j < 64 ? 0xF7351260ull : (j < 124 ? (late ? 0xF75314260ull : 0xF7514603ull) : (hasSlice ? 0xF753426ull : 0xF10ull));
                 plan != 0xF; plan >>= 4) {
                const int step = plan & 15;
                if ((step & 14) == 4) {
                    const int hh = rg + 8 * warp;
                    const uint32_t real = step & 1, both = real & (mat | (warp != 3));
                    if (both) wait_ticket(smem + SM_BAR + W_PROG, mat ? NT + YB : min((33 + hh) * 128 + LAGT, NT + YLATE) + YX);
                    __syncwarp();
                    const float* src = (mat ? G.ctx : G.o) + hh * 128 + lane * 4;
                    uint4 v[2];
                    v[0] = v[1] = make_uint4(tag, tag, tag, tag);
                    uint32_t bad0 = real, bad1 = both;
                    unsigned it = 0;
                    while (true) {
                        ld_relaxed128_if(v[0], src, bad0);
                        ld_relaxed128_if(v[1], src + 4096, bad1);
                        bad0 = bad4(v[0], tag) & 1u; bad1 = bad4(v[1], tag) & 1u;
                        if (!__any_sync(~0u, bad0 | bad1)) break;
                        if (++it > SPIN_LIMIT) __trap();
                    }
#pragma unroll
                    for (int b = 0; b < 2; b++)
                        *(uint2*)(smem + SM_VEC + V_X + b * XSTR + (128 * warp + 4 * lane) * 2) =
                            make_uint2(pack_bf16(__uint_as_float(v[b].x), __uint_as_float(v[b].y)), pack_bf16(__uint_as_float(v[b].z), __uint_as_float(v[b].w)));
                    named_bar(1, 128);
                    STAMP(tid == 0, 29);
                } else if (step >= 6) {
                    const uint32_t real = step & 1;
                    const uint32_t xa = sb + SM_VEC + V_X + ((lane >> 1) & 1) * XSTR + 8 * (lane >> 3) * 2;
                    const uint32_t wa = sb + SM_SQ + 2 * 16384 + (8 * (lane >> 4) + (lane & 7)) * 128 +
                                        (((2 * warp + ((lane >> 3) & 1)) ^ (lane & 7)) << 4);
                    const uint32_t bs = sb + SM_BAR + BAR_S + 16;
                    const float* src = G.o + 4096 + (24 + rg) * 128 + lane * 4;
                    const uint32_t needx = real & (mat ^ 1);
                    uint32_t* dst = (uint32_t*)P.out + (t & 1) * 512 + mat * 256 + cg * 32 + warp * 8 + (t >> 1) * 4 + (g >> 1);
                    asm volatile("" : "+l"(dst));
                    uint4 v = make_uint4(tag, tag, tag, tag);
                    float d[4][4];
#pragma unroll
                    for (int i = 0; i < 16; i++) (&d[0][0])[i] = 0.f;
#pragma unroll 1
                    for (int u = 0; u < 3; u++) {
                        uint4 xf[4];
                        if (needx && u == 2) wait_ticket(smem + SM_BAR + W_PROG, NT + YP);
                        __syncwarp();
                        ld_relaxed128_if(v, src, needx & (u == 2));
#pragma unroll
                        for (int i = 0; i < 4; i++) xf[i] = ldsm4(xa + u * 256 + i * 64);
                        if (real) mbar_wait_nt(bs + u * 8, 0);
#pragma unroll
                        for (int i = 0; i < 4; i++) {
                            const uint4 w0 = ldsm4t(wa + u * 16384 + i * 4096), w1 = ldsm4t(wa + u * 16384 + i * 4096 + 2048);
                            mma16816(d[(i & 1) * 2], w0.x, w0.y, w0.z, w0.w, xf[i].x, xf[i].y);
                            mma16816(d[(i & 1) * 2 + 1], w1.x, w1.y, w1.z, w1.w, xf[i].z, xf[i].w);
                        }
                    }
                    unsigned it = 0;
                    while (__any_sync(~0u, bad4(v, tag) & 1u)) {
                        if (++it > SPIN_LIMIT) __trap();
                        v = ld_relaxed128(src);
                    }
                    STAMP(tid == 96, 20);
                    if (!mat)
                        *(uint2*)(smem + SM_VEC + V_X + XSTR + (384 + 4 * lane) * 2) =
                            make_uint2(pack_bf16(__uint_as_float(v.x), __uint_as_float(v.y)), pack_bf16(__uint_as_float(v.z), __uint_as_float(v.w)));
                    __syncwarp();
                    uint4 xf[4], w[4];
#pragma unroll
                    for (int i = 0; i < 4; i++) xf[i] = ldsm4(xa + 3 * 256 + i * 64);
#pragma unroll
                    for (int q = 0; q < 2; q++) {
                        if (q) {
#pragma unroll
                            for (int i = 0; i < 4; i++) {
                                d[0][i] = (d[0][i] + d[1][i]) + (d[2][i] + d[3][i]);
                                d[1][i] = d[2][i] = d[3][i] = 0.f;
                            }
                        }
                        if (real) mbar_wait_nt(bs + 24 + q * 8, 0);
#pragma unroll
                        for (int i = 0; i < 4; i++) w[i] = ldsm4t(wa + 3 * 16384 + q * 8192 + i * 2048);
#pragma unroll
                        for (int i = 0; i < 2; i++) {
                            mma16816(d[2 * i], w[2 * i].x, w[2 * i].y, w[2 * i].z, w[2 * i].w, xf[2 * q + i].x, xf[2 * q + i].y);
                            mma16816(d[2 * i + 1], w[2 * i + 1].x, w[2 * i + 1].y, w[2 * i + 1].z, w[2 * i + 1].w, xf[2 * q + i].z, xf[2 * q + i].w);
                        }
                    }
                    STAMP(tid == 64, 22);
                    float e[4];
#pragma unroll
                    for (int i = 0; i < 4; i++) e[i] = (t & 2) ? d[i][2] : d[i][0];
                    red_out(dst, ((e[0] + e[1]) + e[2]) + e[3], g, real);
                    STAMP(tid == 64, 13);
                    if (real) asm volatile("exit;");
                } else if (step >= 2) {
                    uint2 bf[16];
                    tall_prep(bf, sb + SM_P, warp, g, t);
                    if (step & 1) mbar_wait(sb + SM_BAR + BAR_S + (warp >> 1) * 8, 0);
                    LAND(tid == 64, 17408 + 3 * 128 + j);
                    gemv_tall(sb + SM_SQ, bf, red + 512, warp, g, t);
                    tall_finish(red + 512, G.ctx + ((tid >> 5) & 1) * 4096 + 32 * j + (tid & 31), tid, tag, 0, (step & 1) ? 64 : 0);
                    STAMP(tid == 0, 12);
                } else {
                    const int b = step;
                    const int hm = min(h, 31), bh = 32 * b + hm;
                    wait_ticket(smem + SM_BAR + W_PROG, min((bh + 1) * 128 + LAGT, NT + YLATE + max(hm - 27, 0) * YSL));
                    __syncwarp();
                    float* rb = red + b * 256;
                    combineA(G, bh, qd, tag, rb, tid, smem + SM_BAR + W_PROG);
                    {
                        if (tid < 32)
                            st_relaxed32(G.o + bh * 128 + 32 * qd + tid, tagw((rb[tid] + rb[32 + tid]) + (rb[64 + tid] + rb[96 + tid]), tag));
                        STAMP(tid == 0, 9 + 2 * b);
                    }
                }
            }
        }
    }
}

typedef CUresult (*EncodeFn)(CUtensorMap*, CUtensorMapDataType, cuuint32_t, void*, const cuuint64_t*, const cuuint64_t*,
                             const cuuint32_t*, const cuuint32_t*, CUtensorMapInterleave, CUtensorMapSwizzle,
                             CUtensorMapL2promotion, CUtensorMapFloatOOBfill);

}

extern "C" void kernel_launch(void* const* d_in, const int* in_sizes, int n_in, void* d_out, int out_size) {
    (void)in_sizes; (void)n_in; (void)out_size;
    static EncodeFn encode = nullptr;
    static void* scratch = nullptr;
    if (!encode) {
        void* fn = nullptr;
        cudaDriverEntryPointQueryResult st;
        cudaGetDriverEntryPoint("cuTensorMapEncodeTiled", &fn, cudaEnableDefault, &st);
        encode = (EncodeFn)fn;
        cudaGetSymbolAddress(&scratch, g_raw);
        cudaFuncSetAttribute(fused_decode_kernel, cudaFuncAttributeMaxDynamicSharedMemorySize, SM_TOTAL);
    }
    Ptrs P;
    Maps M;
    auto mk = [&](CUtensorMap* m, void* ptr, cuuint64_t cols, cuuint64_t rows, cuuint32_t bc, cuuint32_t br, CUtensorMapSwizzle sw,
                  CUtensorMapL2promotion promo) {
        const cuuint64_t gdim[2] = {cols, rows};
        const cuuint64_t gstr[1] = {cols * 2};
        const cuuint32_t box[2] = {bc, br};
        const cuuint32_t estr[2] = {1, 1};
        encode(m, CU_TENSOR_MAP_DATA_TYPE_BFLOAT16, 2, ptr, gdim, gstr, box, estr, CU_TENSOR_MAP_INTERLEAVE_NONE, sw,
               promo, CU_TENSOR_MAP_FLOAT_OOB_FILL_NONE);
    };
    mk(&M.m_wq, d_in[3], 4096, 512, 32, 256, CU_TENSOR_MAP_SWIZZLE_64B, CU_TENSOR_MAP_L2_PROMOTION_NONE);
    auto mk3 = [&](CUtensorMap* m, void* ptr, cuuint64_t cols, cuuint64_t rows) {
        const cuuint64_t gdim[3] = {64, rows, cols / 64};
        const cuuint64_t gstr[2] = {cols * 2, 128};
        const cuuint32_t box[3] = {64, 64, 2};
        const cuuint32_t estr[3] = {1, 1, 1};
        encode(m, CU_TENSOR_MAP_DATA_TYPE_BFLOAT16, 3, ptr, gdim, gstr, box, estr, CU_TENSOR_MAP_INTERLEAVE_NONE,
               CU_TENSOR_MAP_SWIZZLE_128B, CU_TENSOR_MAP_L2_PROMOTION_L2_256B, CU_TENSOR_MAP_FLOAT_OOB_FILL_NONE);
    };
    mk3(&M.m_v, d_in[2], 128, 524288);
    mk(&M.m_uv[0], d_in[9], 4096, 512, 32, 128, CU_TENSOR_MAP_SWIZZLE_64B, CU_TENSOR_MAP_L2_PROMOTION_NONE);
    mk(&M.m_uv[1], d_in[9], 4096, 512, 32, 128, CU_TENSOR_MAP_SWIZZLE_64B, CU_TENSOR_MAP_L2_PROMOTION_L2_256B);
    mk(&M.m_w[0], d_in[4], 512, 4096, 64, 64, CU_TENSOR_MAP_SWIZZLE_128B, CU_TENSOR_MAP_L2_PROMOTION_L2_256B);
    mk(&M.m_w[1], d_in[10], 512, 4096, 64, 64, CU_TENSOR_MAP_SWIZZLE_128B, CU_TENSOR_MAP_L2_PROMOTION_L2_256B);
    mk(&M.m_ckv, d_in[6], 512, 16384, 64, 64, CU_TENSOR_MAP_SWIZZLE_128B, CU_TENSOR_MAP_L2_PROMOTION_L2_256B);
    mk(&M.m_wqB, d_in[7], 4096, 512, 32, 256, CU_TENSOR_MAP_SWIZZLE_64B, CU_TENSOR_MAP_L2_PROMOTION_NONE);
    mk(&M.m_wuk, d_in[8], 4096, 512, 128, 128, CU_TENSOR_MAP_SWIZZLE_NONE, CU_TENSOR_MAP_L2_PROMOTION_L2_256B);
    P.xA = (const __nv_bfloat16*)d_in[0];
    P.K = (const __nv_bfloat16*)d_in[1];
    P.xB = (const __nv_bfloat16*)d_in[5];
    P.out = (__nv_bfloat16*)d_out;
    P.g = (Scratch*)scratch;
    cudaLaunchConfig_t cfg = {};
    cfg.gridDim = dim3(GRID);
    cfg.blockDim = dim3(NTHREADS);
    cfg.dynamicSmemBytes = SM_TOTAL;
    cfg.stream = cudaStreamPerThread;
    cudaLaunchAttribute attr;
    attr.id = cudaLaunchAttributeCooperative;
    attr.val.cooperative = 1;
    cfg.attrs = &attr;
    cfg.numAttrs = 1;
    cudaLaunchKernelEx(&cfg, fused_decode_kernel, P, M);
}
```

```cpp
#include <cuda_runtime.h>
#include <cuda_bf16.h>
#include <cuda.h>
#include <stdint.h>

namespace {

constexpr int NT       = 8192;
constexpr int GRID     = 132;
constexpr int NB_CTA   = 16;
constexpr int NA_CTA   = GRID - NB_CTA;
constexpr int NWORK    = 3;
#define YV 292
#define DV 54
#define YW 407
#define DW 68
#define DL 6
#define YX 150
#define YB 582
#define YP 605
#define XRV 330
#define TV 3200
#define PFB 8192
#define LAGT 1060
#define YLATE 120
#define YSL 70
#define YO 450
#define YOS 40
#define TUV (43 * 128)
#define XPK 80
#define FRZ 300
#define GLOOK 120
#define QDELAY 500
constexpr int NEARX = 400;
constexpr int GN = 8, GST = 16;
constexpr int JE0   = 112;
constexpr int HCLR  = 26;
constexpr int BINFL = 2;
constexpr int NSTATIC  = NA_CTA * NWORK;
constexpr unsigned DRAWS = (NT - NSTATIC) + GRID * NWORK;
static_assert(52 * 128 + LAGT + 300 <= NT && TUV + 10 * 128 <= NT, "wait_prog thresholds must be reachable");
constexpr int NTHREADS = 256;
constexpr float SCALE = 0.08838834764831845f, LOG2E = 1.4426950408889634f;
constexpr unsigned SPIN_LIMIT = 1u << 22;

constexpr int SM_SLOT  = 0;
constexpr int SM_QA    = 196608;
constexpr int SM_P     = SM_QA + 16384;
constexpr int SM_RED1  = SM_P + 4096;
constexpr int SM_RED2  = SM_RED1 + 2048;
constexpr int SM_VEC   = SM_RED2 + 4096;
constexpr int SM_BAR   = SM_VEC + 3072;
constexpr int SM_TOTAL = SM_BAR + 352;
constexpr int V_X    = 512;
constexpr int BAR_FULL = 0;
constexpr int BAR_PDONE= 48;
constexpr int BAR_BDONE= 56;
constexpr int BAR_QABS = 72;
constexpr int BAR_BFULL= 80;
constexpr int BAR_BEMPTY=120;
constexpr int BAR_WFREE= 160;
constexpr int BAR_W    = 168;
constexpr int BAR_S    = 192;
constexpr int BAR_Q    = 264;
constexpr int W_EPOCH  = 328;
constexpr int W_PROG   = 336;
constexpr int SM_WQ = 3 * 32768, SM_WQB = 4 * 32768, SM_WUK = 5 * 32768;
constexpr int SM_SQ = 3 * 32768;
constexpr int XSTR = 1024 + 16;

struct __align__(128) Cnt { unsigned v; unsigned pad[31]; };
struct __align__(128) Scratch {
    Cnt epoch, ticket, cntQabs, cntB;
    float qA[64 * 128], qB[64 * 128];
    __nv_bfloat16 qabs[2 * 32 * 512];
    float  partO[NT * 128];
    float2 partML[NT * 4];
    float  bpart[NB_CTA * 32 * 512];
    float2 bml[NB_CTA * 32];
    float  ctx[32 * 4 * 2 * 128];
    float  o[2 * 4096];
    Cnt    clk;
};
__device__ __align__(128) unsigned char g_raw[sizeof(Scratch)];

__device__ __forceinline__ int slice_of(int cta) {
    return cta >= 128 ? cta : ((cta & 8) << 3) | ((cta >> 4) << 3) | (cta & 7);
}

#define STAMP(cond, i) do {} while (0)
#define LAND(cond, i) do {} while (0)

__device__ __forceinline__ void mbar_init(uint32_t bar, int cnt) {
    asm volatile("mbarrier.init.shared::cta.b64 [%0], %1;" ::"r"(bar), "r"(cnt) : "memory");
}
__device__ __forceinline__ void mbar_expect_tx(uint32_t bar, uint32_t bytes) {
    asm volatile("mbarrier.arrive.expect_tx.shared::cta.b64 _, [%0], %1;" ::"r"(bar), "r"(bytes) : "memory");
}
__device__ __forceinline__ void mbar_arrive(uint32_t bar) {
    asm volatile("mbarrier.arrive.shared::cta.b64 _, [%0];" ::"r"(bar) : "memory");
}
__device__ __forceinline__ void mbar_wait(uint32_t bar, uint32_t parity) {
    unsigned it = 0;
    while (true) {
        uint32_t ok;
        asm volatile("{\n.reg .pred p;\nmbarrier.try_wait.parity.shared::cta.b64 p, [%1], %2;\nselp.u32 %0, 1, 0, p;\n}\n"
                     : "=r"(ok) : "r"(bar), "r"(parity) : "memory");
        if (ok) break;
        if (++it > SPIN_LIMIT) __trap();
    }
}
__device__ __forceinline__ void mbar_wait_nt(uint32_t bar, uint32_t parity) {
#pragma unroll 1
    for (unsigned it = 0; it < SPIN_LIMIT; it++) {
        uint32_t ok;
        asm volatile("{\n.reg .pred p;\nmbarrier.try_wait.parity.shared::cta.b64 p, [%1], %2;\nselp.u32 %0, 1, 0, p;\n}\n"
                     : "=r"(ok) : "r"(bar), "r"(parity) : "memory");
        if (ok) break;
    }
}
__device__ __forceinline__ bool mbar_test(uint32_t bar, uint32_t parity) {
    uint32_t ok;
    asm volatile("{\n.reg .pred p;\nmbarrier.test_wait.parity.shared::cta.b64 p, [%1], %2;\nselp.u32 %0, 1, 0, p;\n}\n"
                 : "=r"(ok) : "r"(bar), "r"(parity) : "memory");
    return ok;
}
__device__ __forceinline__ void bulk_load(uint32_t dst, const void* src, uint32_t bytes, uint32_t bar, uint64_t pol) {
    asm volatile("cp.async.bulk.shared::cluster.global.mbarrier::complete_tx::bytes.L2::cache_hint [%0], [%1], %2, [%3], %4;"
                 ::"r"(dst), "l"(src), "r"(bytes), "r"(bar), "l"(pol) : "memory");
}
__device__ __forceinline__ void bulk_load_nohint(uint32_t dst, const void* src, uint32_t bytes, uint32_t bar) {
    asm volatile("cp.async.bulk.shared::cluster.global.mbarrier::complete_tx::bytes [%0], [%1], %2, [%3];"
                 ::"r"(dst), "l"(src), "r"(bytes), "r"(bar) : "memory");
}
__device__ __forceinline__ void tma_2d(uint32_t dst, const CUtensorMap* map, int c0, int c1, uint32_t bar, uint64_t pol) {
    asm volatile("cp.async.bulk.tensor.2d.shared::cluster.global.mbarrier::complete_tx::bytes.L2::cache_hint [%0], [%1, {%3, %4}], [%2], %5;"
                 ::"r"(dst), "l"(map), "r"(bar), "r"(c0), "r"(c1), "l"(pol) : "memory");
}
__device__ __forceinline__ void tma_3d(uint32_t dst, const CUtensorMap* map, int c1, int c2, uint32_t bar, uint64_t pol) {
    asm volatile("cp.async.bulk.tensor.3d.shared::cluster.global.mbarrier::complete_tx::bytes.L2::cache_hint [%0], [%1, {%3, %4, %5}], [%2], %6;"
                 ::"r"(dst), "l"(map), "r"(bar), "r"(0), "r"(c1), "r"(c2), "l"(pol) : "memory");
}
__device__ __forceinline__ void wait_prog(const unsigned char* smem_word, unsigned th) {
    unsigned it = 0;
    while (*(volatile const unsigned*)(smem_word + 8) + NSTATIC < th) {
        __nanosleep(60);
        if (++it > SPIN_LIMIT) __trap();
    }
}
__device__ __forceinline__ uint32_t now_ns() {
    uint32_t t;
    asm volatile("mov.u32 %0, %globaltimer_lo;" : "=r"(t) :: "memory");
    return t;
}
__device__ __forceinline__ void note_draw(unsigned char* smem_word, unsigned raw, unsigned* clk, uint32_t tag) {
    const uint32_t a = (uint32_t)__cvta_generic_to_shared(smem_word);
    asm volatile("st.volatile.u32 [%0], %1;" ::"l"(smem_word + 8), "r"(raw) : "memory");
    const uint32_t now = now_ns();
    if ((int)raw < NT - NSTATIC - FRZ) asm volatile("st.volatile.shared.v2.u32 [%0], {%1, %2};" ::"r"(a), "r"(raw), "r"(now) : "memory");
    const unsigned q = NT - NSTATIC - FRZ - raw;
    if ((q & ~((GN - 1) * GST)) == 0)
        asm volatile("st.relaxed.gpu.global.u32 [%0], %1;" ::"l"(clk + q / GST), "r"(((now + q * 10) & ~1u) | tag) : "memory");
}
__device__ __forceinline__ void wait_ticket(const unsigned char* smem_word, int th) {
    wait_prog(smem_word, min(th, NT - NEARX));
    uint32_t tk, t0;
#pragma unroll 1
    for (unsigned it = 0; it < SPIN_LIMIT; it++) {
        asm volatile("ld.volatile.shared.v2.u32 {%0, %1}, [%2];" : "=r"(tk), "=r"(t0) : "r"((uint32_t)__cvta_generic_to_shared(smem_word)) : "memory");
        if ((int)(now_ns() - t0) >= (th - NSTATIC - (int)tk) * 10) break;
        __nanosleep(20);
    }
}
__device__ __forceinline__ bool mbar_wait_for(uint32_t bar, uint32_t parity, int n) {
    uint32_t c0, c;
    asm volatile("mov.u32 %0, %%clock;" : "=r"(c0) :: "memory");
    do {
        if (mbar_test(bar, parity)) return true;
        asm volatile("mov.u32 %0, %%clock;" : "=r"(c) :: "memory");
    } while ((int)(c - c0) < n);
    return false;
}
__device__ __forceinline__ bool elect_one() {
    uint32_t p;
    asm volatile("{\n.reg .pred p;\nelect.sync _|p, 0xffffffff;\nselp.u32 %0, 1, 0, p;\n}\n" : "=r"(p));
    return p;
}
__device__ __forceinline__ void fence_proxy_async() { asm volatile("fence.proxy.async;" ::: "memory"); }
__device__ __forceinline__ void named_bar(int id, int n) { asm volatile("bar.sync %0, %1;" ::"r"(id), "r"(n) : "memory"); }

__device__ __forceinline__ uint4 lds128(uint32_t a) {
    uint4 v;
    asm volatile("ld.shared.v4.u32 {%0,%1,%2,%3}, [%4];" : "=r"(v.x), "=r"(v.y), "=r"(v.z), "=r"(v.w) : "r"(a));
    return v;
}
__device__ __forceinline__ uint4 ldsm4(uint32_t a) {
    uint4 v;
    asm volatile("ldmatrix.sync.aligned.m8n8.x4.shared.b16 {%0,%1,%2,%3}, [%4];" : "=r"(v.x), "=r"(v.y), "=r"(v.z), "=r"(v.w) : "r"(a));
    return v;
}
__device__ __forceinline__ uint4 ldsm4t(uint32_t a) {
    uint4 v;
    asm volatile("ldmatrix.sync.aligned.m8n8.x4.trans.shared.b16 {%0,%1,%2,%3}, [%4];" : "=r"(v.x), "=r"(v.y), "=r"(v.z), "=r"(v.w) : "r"(a));
    return v;
}
__device__ __forceinline__ uint2 lds64(uint32_t a) {
    uint2 v;
    asm volatile("ld.shared.v2.u32 {%0,%1}, [%2];" : "=r"(v.x), "=r"(v.y) : "r"(a));
    return v;
}
__device__ __forceinline__ uint4 ld_relaxed128(const void* p) {
    uint4 v;
    asm volatile("ld.relaxed.gpu.global.v4.u32 {%0,%1,%2,%3}, [%4];" : "=r"(v.x), "=r"(v.y), "=r"(v.z), "=r"(v.w) : "l"(p) : "memory");
    return v;
}
__device__ __forceinline__ uint2 ld_relaxed64(const void* p) {
    uint2 v;
    asm volatile("ld.relaxed.gpu.global.v2.u32 {%0,%1}, [%2];" : "=r"(v.x), "=r"(v.y) : "l"(p) : "memory");
    return v;
}
__device__ __forceinline__ uint32_t ld_relaxed32(const void* p) {
    uint32_t v;
    asm volatile("ld.relaxed.gpu.global.u32 %0, [%1];" : "=r"(v) : "l"(p) : "memory");
    return v;
}
__device__ __forceinline__ uint32_t ld_acquire32(const void* p) {
    uint32_t v;
    asm volatile("ld.acquire.gpu.global.u32 %0, [%1];" : "=r"(v) : "l"(p) : "memory");
    return v;
}
__device__ __forceinline__ void st_relaxed128(void* p, uint32_t a, uint32_t b, uint32_t c, uint32_t d) {
    asm volatile("st.relaxed.gpu.global.v4.u32 [%0], {%1,%2,%3,%4};" ::"l"(p), "r"(a), "r"(b), "r"(c), "r"(d) : "memory");
}
__device__ __forceinline__ void red_release(unsigned* p) {
    asm volatile("red.release.gpu.global.add.u32 [%0], 1;" ::"l"(p) : "memory");
}
__device__ __forceinline__ void wait_counter(const unsigned* p, unsigned target, unsigned ns) {
    unsigned it = 0;
    while ((int)(ld_acquire32(p) - target) < 0) {
        __nanosleep(ns);
        if (++it > SPIN_LIMIT) __trap();
    }
}
__device__ __forceinline__ uint32_t prmt(uint32_t a, uint32_t b, uint32_t s) {
    uint32_t d;
    asm("prmt.b32 %0, %1, %2, %3;" : "=r"(d) : "r"(a), "r"(b), "r"(s));
    return d;
}
__device__ __forceinline__ uint32_t pack_bf16(float lo, float hi) {
    uint32_t d;
    asm("cvt.rn.bf16x2.f32 %0, %1, %2;" : "=r"(d) : "f"(hi), "f"(lo));
    return d;
}
__device__ __forceinline__ float ex2(float x) {
    float y;
    asm("ex2.approx.ftz.f32 %0, %1;" : "=f"(y) : "f"(x));
    return y;
}
__device__ __forceinline__ float bf_lo(uint32_t v) { return __uint_as_float(v << 16); }
__device__ __forceinline__ float bf_hi(uint32_t v) { return __uint_as_float(v & 0xffff0000u); }
__device__ __forceinline__ void scale_scores(float& a, float& b) {
    uint32_t p = pack_bf16(a, b);
    p = pack_bf16(bf_lo(p) * SCALE, bf_hi(p) * SCALE);
    a = bf_lo(p); b = bf_hi(p);
}
__device__ __forceinline__ uint32_t tagw(float v, uint32_t tag) {
    uint32_t d;
    asm("lop3.b32 %0, %1, 0xfffffffe, %2, 0xEA;" : "=r"(d) : "r"(__float_as_uint(v)), "r"(tag));
    return d;
}
__device__ __forceinline__ uint32_t bad2(uint32_t x, uint32_t y, uint32_t tag) {
    uint32_t d;
    asm("lop3.b32 %0, %1, %2, %3, 0x7E;" : "=r"(d) : "r"(x), "r"(y), "r"(tag));
    return d;
}
__device__ __forceinline__ uint32_t bad4(const uint4& v, uint32_t tag) { return bad2(v.x, v.y, tag) | bad2(v.z, v.w, tag); }
__device__ __forceinline__ void ld_relaxed128_if(uint4& v, const void* p, uint32_t c) {
    asm volatile("{\n.reg .pred p;\nsetp.ne.u32 p, %5, 0;\n@p ld.relaxed.gpu.global.v4.u32 {%0,%1,%2,%3}, [%4];\n}\n"
                 : "+r"(v.x), "+r"(v.y), "+r"(v.z), "+r"(v.w) : "l"(p), "r"(c) : "memory");
}
__device__ __forceinline__ void ld_relaxed64_if(uint2& v, const void* p, uint32_t c) {
    asm volatile("{\n.reg .pred p;\nsetp.ne.u32 p, %3, 0;\n@p ld.relaxed.gpu.global.v2.u32 {%0,%1}, [%2];\n}\n"
                 : "+r"(v.x), "+r"(v.y) : "l"(p), "r"(c) : "memory");
}
__device__ __forceinline__ void st_relaxed32(void* p, uint32_t a) {
    asm volatile("st.relaxed.gpu.global.u32 [%0], %1;" ::"l"(p), "r"(a) : "memory");
}
__device__ __forceinline__ void red_out(uint32_t* word, float v, int col, uint32_t go) {
    const uint32_t pk = (col & 1) ? pack_bf16(-0.f, v) : pack_bf16(v, -0.f);
    asm volatile("{\n.reg .pred p;\nsetp.ne.u32 p, %2, 0;\n@p red.relaxed.gpu.global.add.noftz.bf16x2 [%0], %1;\n}\n"
                 ::"l"(word), "r"(pk), "r"(go) : "memory");
}
__device__ __forceinline__ void mma16816(float (&c)[4], uint32_t a0, uint32_t a1, uint32_t a2, uint32_t a3,
                                         uint32_t b0, uint32_t b1) {
    asm("mma.sync.aligned.m16n8k16.row.col.f32.bf16.bf16.f32 {%0,%1,%2,%3}, {%4,%5,%6,%7}, {%8,%9}, {%0,%1,%2,%3};"
        : "+f"(c[0]), "+f"(c[1]), "+f"(c[2]), "+f"(c[3])
        : "r"(a0), "r"(a1), "r"(a2), "r"(a3), "r"(b0), "r"(b1));
}
__device__ __forceinline__ uint64_t make_desc(uint32_t addr) {
    return (uint64_t)((addr & 0x3FFFF) >> 4) | ((uint64_t)1 << 16) | ((uint64_t)64 << 32) | ((uint64_t)1 << 62);
}
template <int TRANS_A>
__device__ __forceinline__ void wgmma_n32(float (&d)[16], uint64_t da, uint64_t db, int scale_d) {
    asm volatile("{\n.reg .pred p;\nsetp.ne.b32 p, %18, 0;\n"
                 "wgmma.mma_async.sync.aligned.m64n32k16.f32.bf16.bf16 "
                 "{%0,%1,%2,%3,%4,%5,%6,%7,%8,%9,%10,%11,%12,%13,%14,%15}, %16, %17, p, 1, 1, %19, 0;\n}\n"
                 : "+f"(d[0]), "+f"(d[1]), "+f"(d[2]), "+f"(d[3]), "+f"(d[4]), "+f"(d[5]), "+f"(d[6]), "+f"(d[7]),
                   "+f"(d[8]), "+f"(d[9]), "+f"(d[10]), "+f"(d[11]), "+f"(d[12]), "+f"(d[13]), "+f"(d[14]), "+f"(d[15])
                 : "l"(da), "l"(db), "r"(scale_d), "n"(TRANS_A));
}
__device__ __forceinline__ void wg_fence()  { asm volatile("wgmma.fence.sync.aligned;" ::: "memory"); }
__device__ __forceinline__ void wg_commit() { asm volatile("wgmma.commit_group.sync.aligned;" ::: "memory"); }
template <int N> __device__ __forceinline__ void wg_wait() { asm volatile("wgmma.wait_group.sync.aligned %0;" ::"n"(N) : "memory"); }

__device__ __forceinline__ void issue_tall(uint32_t dst, const CUtensorMap* map, int col, int row, uint32_t bar, uint64_t pol) {
    tma_2d(dst, map, col, row, bar, pol);
    tma_2d(dst + 16384, map, col, row + 256, bar, pol);
}
__device__ __forceinline__ void tall_prep(uint2 (&bf)[16], uint32_t xbase, int w4, int g, int t) {
    const uint32_t xp = xbase + ((g >> 1) & 1) * 1024 + w4 * 256 + (t >> 1) * 8;
    const uint32_t sel = (g & 1) ? ((t & 1) ? 0x3244u : 0x1044u) : ((t & 1) ? 0x4432u : 0x4410u);
#pragma unroll
    for (int i = 0; i < 16; i++) {
        const uint2 xw = lds64(xp + i * 16);
        bf[i] = make_uint2(prmt(xw.x, 0, sel), prmt(xw.y, 0, sel));
    }
}
__device__ __forceinline__ void gemv_tall(uint32_t wbase, const uint2 (&bf)[16], float* red, int w4, int g, int t) {
    const uint32_t wu = wbase + (128 * w4 + (t & 1) + 4 * (t >> 1)) * 64 + (((g >> 1) ^ (t & 2)) << 4) + (g & 1) * 8;
    const uint32_t wv = (wu + 128) ^ 16;
    float a[4][4];
#pragma unroll
    for (int i = 0; i < 16; i++) (&a[0][0])[i] = 0.f;
#pragma unroll
    for (int i = 0; i < 16; i++) {
        const uint2 u = lds64(wu + i * 512), v = lds64(wv + i * 512);
        mma16816(a[i & 3], u.x, u.y, v.x, v.y, bf[i].x, bf[i].y);
    }
    if (t < 2)
        *(float4*)(red + (w4 * 2 + t) * 32 + 4 * g) =
            make_float4((a[0][0] + a[1][0]) + (a[2][0] + a[3][0]), (a[0][1] + a[1][1]) + (a[2][1] + a[3][1]),
                        (a[0][2] + a[1][2]) + (a[2][2] + a[3][2]), (a[0][3] + a[1][3]) + (a[2][3] + a[3][3]));
}
__device__ __forceinline__ void tall_finish(const float* red, float* dst, int tid, uint32_t tag, int lo = 0, int hi = 64) {
    named_bar(1, 128);
    if (tid >= lo && tid < hi) {
        st_relaxed32(dst, tagw((red[tid] + red[64 + tid]) + (red[128 + tid] + red[192 + tid]), tag));
    }
}

__device__ __forceinline__ void combineA(Scratch& G, int bh, int dq, uint32_t tag, float* red, int tid, const unsigned char* prog) {
    const int r = tid >> 3, c4 = tid & 7, w4 = tid >> 5, lane = tid & 31;
    const float2* ml = G.partML + (bh * 128 + r) * 4;
    const float* po = G.partO + (size_t)(bh * 128 + r) * 128 + dq * 32 + c4 * 4;
    uint2 m[8];
    uint4 o[8];
    uint32_t bad[8];
    STAMP(tid == 0 && bh >= 32, 28);
#pragma unroll
    for (int k = 0; k < 8; k++) m[k] = ld_relaxed64(ml + 64 * k);
#pragma unroll
    for (int k = 0; k < 8; k++) {
        o[k] = make_uint4(~tag, ~tag, ~tag, ~tag);
        ld_relaxed128_if(o[k], po + (size_t)k * 16 * 128, bh < 60);
    }
    unsigned it = 0;
    while (true) {
        uint32_t any = 0;
#pragma unroll
        for (int k = 0; k < 8; k++) { bad[k] = bad2(m[k].x, m[k].y, tag) & 1u; any |= bad[k]; }
        if (!__any_sync(~0u, any)) break;
#pragma unroll
        for (int k = 0; k < 8; k++) ld_relaxed64_if(m[k], ml + 64 * k, bad[k]);
        if (++it > SPIN_LIMIT) __trap();
    }
    STAMP(tid == 0 && bh >= 32, 30);
    STAMP(tid == 0 && bh >= 32, 19);
    float M = fmaxf(fmaxf(fmaxf(__uint_as_float(m[0].x), __uint_as_float(m[1].x)), fmaxf(__uint_as_float(m[2].x), __uint_as_float(m[3].x))),
                    fmaxf(fmaxf(__uint_as_float(m[4].x), __uint_as_float(m[5].x)), fmaxf(__uint_as_float(m[6].x), __uint_as_float(m[7].x))));
    M = fmaxf(M, __shfl_xor_sync(~0u, M, 8));
    M = fmaxf(M, __shfl_xor_sync(~0u, M, 16));
    float wgt[8], L = 0.f;
#pragma unroll
    for (int k = 0; k < 8; k++) {
        wgt[k] = ex2(__uint_as_float(m[k].x) - M);
        L = fmaf(wgt[k], __uint_as_float(m[k].y), L);
    }
    L += __shfl_xor_sync(~0u, L, 8);
    L += __shfl_xor_sync(~0u, L, 16);
    if (lane == 0) { red[128 + w4] = M; red[132 + w4] = L; }
    named_bar(1, 128);
    {
        const float4 Mw = *(float4*)(red + 128), Lw = *(float4*)(red + 132);
        const float Mx = fmaxf(fmaxf(Mw.x, Mw.y), fmaxf(Mw.z, Mw.w));
        const float Lt = (ex2(Mw.x - Mx) * Lw.x + ex2(Mw.y - Mx) * Lw.y) + (ex2(Mw.z - Mx) * Lw.z + ex2(Mw.w - Mx) * Lw.w);
        const float f = ex2(M - Mx) / Lt;
#pragma unroll
        for (int k = 0; k < 8; k++) wgt[k] *= f;
    }
    STAMP(tid == 0 && bh >= 32, 23);
    if (bh >= 60) wait_ticket(prog, NT + YO + (bh - 63) * YOS);
    while (true) {
        uint32_t any = 0;
#pragma unroll
        for (int k = 0; k < 8; k++) { bad[k] = bad4(o[k], tag) & 1u; any |= bad[k]; }
        if (!__any_sync(~0u, any)) break;
#pragma unroll
        for (int k = 0; k < 8; k++) ld_relaxed128_if(o[k], po + (size_t)k * 16 * 128, bad[k]);
        if (++it > SPIN_LIMIT) __trap();
    }
    STAMP(tid == 0 && bh >= 32, 31);
    float a0 = 0.f, a1 = 0.f, a2 = 0.f, a3 = 0.f, b0 = 0.f, b1 = 0.f, b2 = 0.f, b3 = 0.f;
#pragma unroll
    for (int k = 0; k < 8; k += 2) {
        a0 = fmaf(wgt[k], __uint_as_float(o[k].x), a0); b0 = fmaf(wgt[k + 1], __uint_as_float(o[k + 1].x), b0);
        a1 = fmaf(wgt[k], __uint_as_float(o[k].y), a1); b1 = fmaf(wgt[k + 1], __uint_as_float(o[k + 1].y), b1);
        a2 = fmaf(wgt[k], __uint_as_float(o[k].z), a2); b2 = fmaf(wgt[k + 1], __uint_as_float(o[k + 1].z), b2);
        a3 = fmaf(wgt[k], __uint_as_float(o[k].w), a3); b3 = fmaf(wgt[k + 1], __uint_as_float(o[k + 1].w), b3);
    }
    a0 += b0; a1 += b1; a2 += b2; a3 += b3;
#pragma unroll
    for (int s = 8; s <= 16; s <<= 1) {
        a0 += __shfl_xor_sync(~0u, a0, s);
        a1 += __shfl_xor_sync(~0u, a1, s);
        a2 += __shfl_xor_sync(~0u, a2, s);
        a3 += __shfl_xor_sync(~0u, a3, s);
    }
    if (lane < 8) *(float4*)(red + w4 * 32 + c4 * 4) = make_float4(a0, a1, a2, a3);
    named_bar(1, 128);
    STAMP(tid == 0 && bh >= 32, 24);
}

struct Ptrs {
    const __nv_bfloat16 *K, *xA, *xB;
    __nv_bfloat16* out;
    Scratch* g;
};
struct Maps { CUtensorMap m_wq, m_v, m_ckv, m_wqB, m_wuk, m_uv[2], m_w[2]; };

__global__ void __launch_bounds__(NTHREADS, 1)
fused_decode_kernel(const Ptrs P, const __grid_constant__ Maps M) {
    extern __shared__ __align__(1024) unsigned char smem[];
    const uint32_t sb = (uint32_t)__cvta_generic_to_shared(smem);
    uint64_t pol;
    asm("createpolicy.fractional.L2::evict_first.b64 %0, 1.0;" : "=l"(pol));
    asm volatile("{\n.reg .pred p;\nsetp.lt.u32 p, %3, 32;\n@p cp.async.bulk.prefetch.L2.global.L2::cache_hint [%0], %1, %2;\n}\n"
                 ::"l"((const char*)P.K + (blockIdx.x << 14)), "n"(PFB), "l"(pol), "r"(threadIdx.x) : "memory");
    if (threadIdx.x < 32 && elect_one()) {
        mbar_init(sb + SM_BAR + BAR_FULL, 1);
        mbar_init(sb + SM_BAR + BAR_W, 1);
        asm volatile("fence.mbarrier_init.release.cluster;" ::: "memory");
        if (blockIdx.x < NA_CTA) {
            mbar_expect_tx(sb + SM_BAR + BAR_FULL, 16384);
            bulk_load(sb + SM_SLOT, (const char*)P.K + (blockIdx.x << 14), 16384, sb + SM_BAR + BAR_FULL, pol);
        }
        if (blockIdx.x < 128) {
            mbar_expect_tx(sb + SM_BAR + BAR_W, 32768 + 4096);
            issue_tall(sb + SM_WQ, &M.m_wq, slice_of(blockIdx.x) * 32, 0, sb + SM_BAR + BAR_W, pol);
            bulk_load_nohint(sb + SM_P, P.xA, 2048, sb + SM_BAR + BAR_W);
            bulk_load_nohint(sb + SM_P + 2048, P.xB, 2048, sb + SM_BAR + BAR_W);
        }
    }
    const int tid = threadIdx.x, warp = __shfl_sync(~0u, tid >> 5, 0), lane = tid & 31;
    const int g = lane >> 2, t = lane & 3;
    const int cta = blockIdx.x;
    Scratch& G = *P.g;
    const bool isB = cta >= NA_CTA;
    const bool hasSlice = cta < 128;
    const int j = slice_of(cta), h = j >> 2, qd = cta & 3;
    const int mat = j >> 6, cg = j & 7, rg = (j >> 3) & 7;
    const bool late = j < JE0 || j >= 124;
    STAMP(tid == 32, 0);
    if (warp == 7) {
        __syncthreads();
        const uint32_t epoch = *(volatile uint32_t*)(smem + SM_BAR + W_EPOCH);
        const uint32_t tag = (epoch + 1) & 1;
        if (!isB) { mbar_wait(sb + SM_BAR + BAR_W, 0); __nanosleep(QDELAY); }
#pragma unroll 1
        for (int i = 0; i < 8; i++) {
            if (i == 4 && !isB) wait_prog(smem + SM_BAR + W_PROG, 16 * 128);
            if (i == 0 && isB) { mbar_wait(sb + SM_BAR + BAR_QABS, 0); __nanosleep(8000); }
            uint4 v[8];
            uint32_t bad[8];
#pragma unroll
            for (int k = 0; k < 8; k++) { bad[k] = 1; v[k] = make_uint4(0, 0, 0, 0); }
            unsigned it = 0;
            while (true) {
#pragma unroll
                for (int k = 0; k < 8; k++) ld_relaxed128_if(v[k], G.qA + (8 * i + k) * 128 + lane * 4, bad[k]);
                uint32_t any = 0;
#pragma unroll
                for (int k = 0; k < 8; k++) { bad[k] = bad4(v[k], tag) & 1u; any |= bad[k]; }
                if (!__any_sync(~0u, any)) break;
                __nanosleep(40);
                if (++it > SPIN_LIMIT) __trap();
            }
#pragma unroll
            for (int k = 0; k < 8; k++) {
                uint32_t* dst = (uint32_t*)(smem + SM_QA + (8 * i + k) * 256 + (lane >> 1) * 16 + (lane & 1) * 4);
                dst[0] = pack_bf16(__uint_as_float(v[k].x), __uint_as_float(v[k].y));
                dst[2] = pack_bf16(__uint_as_float(v[k].z), __uint_as_float(v[k].w));
            }
            __syncwarp();
            if (lane == 0) mbar_arrive(sb + SM_BAR + BAR_Q + i * 8);
            STAMP(lane == 0 && i == 0, 2);
        }
        STAMP(lane == 0, 21);
        if (hasSlice) mbar_wait(sb + SM_BAR + BAR_PDONE, 0);
#pragma unroll 1
        for (int p = 0; p < 12; p++) {
            const bool uv = p < 4;
            if (p == (late ? 0 : 4)) {
                wait_ticket(smem + SM_BAR + W_PROG, NT - FRZ + GLOOK);
                uint32_t v;
                unsigned it = 0;
                while (true) {
                    v = ld_relaxed32(&G.clk.v + (lane & (GN - 1)));
                    if (!__any_sync(~0u, (v ^ tag) & 1u)) break;
                    __nanosleep(200);
                    if (++it > SPIN_LIMIT) __trap();
                }
                const uint32_t v0 = __shfl_sync(~0u, v, 0);
                v = v0 + (__reduce_add_sync(~0u, (int)(v - v0)) >> 5);
                if (lane == 0)
                    asm volatile("st.volatile.shared.v2.u32 [%0], {%1, %2};" ::"r"(sb + SM_BAR + W_PROG), "r"(NT - NSTATIC - FRZ), "r"(v) : "memory");
                __syncwarp();
                if (!hasSlice) break;
            }
            if (lane == 0) {
                const int r = uv ? p * 128 : (p - 4) * 64;
                if (!uv || late)
                    wait_ticket(smem + SM_BAR + W_PROG, NT + (uv ? YV + (p * DV >> 1) : YW + ((p - 4) * DW >> 1) + (p == 11 ? DL : 0)));
                STAMP(p == 4, 10);
                const uint32_t bar = sb + SM_BAR + BAR_S + (p < 11 ? p >> 1 : 6) * 8;
                if (!(p & 1) || p == 11) mbar_expect_tx(bar, p < 10 ? 16384 : 8192);
                tma_2d(sb + SM_SQ + p * 8192, uv ? &M.m_uv[late] : &M.m_w[mat], uv ? j * 32 : cg * 64,
                       uv ? r : (rg + 8 * (r >> 7)) * 128 + (r & 127), bar, pol);
            }
            __syncwarp();
        }
    } else if (warp >= 4) {
        const int wi = warp - 4;
        const uint32_t slot = sb + SM_SLOT + wi * 32768;
        const uint32_t bar = sb + SM_BAR + BAR_FULL + wi * 16, barV = bar + 8;
        unsigned tk = wi * NA_CTA + cta;
        const int ev = wi;
        if (lane == 0) {
            if (wi) mbar_init(bar, 1);
            mbar_init(barV, 1);
            if (isB && wi == 0) {
                for (int s = 0; s < 5; s++) {
                    mbar_init(sb + SM_BAR + BAR_BFULL + s * 8, 1);
                    mbar_init(sb + SM_BAR + BAR_BEMPTY + s * 8, 4);
                }
            }
            asm volatile("fence.mbarrier_init.release.cluster;" ::: "memory");
        }
        __syncthreads();
        const uint32_t epoch = *(volatile uint32_t*)(smem + SM_BAR + W_EPOCH);
        const uint32_t tag = (epoch + 1) & 1;

        bool active = true;
        if (isB) {
            if (wi == 1 && lane == 0) {
                wait_counter(&G.cntQabs.v, (epoch + 1) * 128, 64);
                fence_proxy_async();
                mbar_expect_tx(sb + SM_BAR + BAR_QABS, 32768);
                bulk_load_nohint(sb + SM_SLOT + 5 * 32768, G.qabs + ((cta - NA_CTA) >> 3) * 16384, 32768, sb + SM_BAR + BAR_QABS);
            }
            if (wi == 0 && lane == 0) {
                const int ib = cta - NA_CTA;
                int s = 0, sl = 0; uint32_t ph = 1, phl = 0;
                for (int u = 0; u < 32; u++) {
                    if (u >= BINFL) {
                        mbar_wait(sb + SM_BAR + BAR_BFULL + sl * 8, phl);
                        LAND(true, 16384 + ib * 32 + u);
                        if (++sl == 5) { sl = 0; phl ^= 1; }
                    }
                    if (u == 3 && hasSlice) mbar_wait(sb + SM_BAR + BAR_WFREE, 0);
                    mbar_wait(sb + SM_BAR + BAR_BEMPTY + s * 8, ph);
                    const uint32_t fb = sb + SM_BAR + BAR_BFULL + s * 8;
                    const int row = (ib >> 3) * 8192 + ((u >> 1) * 8 + (ib & 7)) * 64;
                    mbar_expect_tx(fb, 32768);
                    for (int x = 0; x < 4; x++)
                        tma_2d(sb + SM_SLOT + s * 32768 + x * 8192, &M.m_ckv, ((u & 1) * 4 + x) * 64, row, fb, pol);
                    if (++s == 5) { s = 0; ph ^= 1; }
                }
            }
            __syncwarp();
            mbar_wait(sb + SM_BAR + BAR_BDONE, 0);
            if (lane == 0) {
                tk = atomicInc(&G.ticket.v, DRAWS - 1);
                note_draw(smem + SM_BAR + W_PROG, tk, &G.clk.v, tag);
                tk += NSTATIC;
            }
            tk = __shfl_sync(~0u, tk, 0);
            active = tk < NT;
        } else if (ev != 0) {
            __syncwarp();
            mbar_wait(sb + SM_BAR + BAR_W + (ev - 1) * 8, 0);
        }
        if (active) {
            if ((isB || ev != 0) && lane == 0) {
                mbar_expect_tx(bar, 16384);
                bulk_load(slot, (const char*)P.K + (size_t)tk * 16384, 16384, bar, pol);
            }
            const uint32_t kA = slot + g * 256 + t * 16 + (g & 1) * 64, kB = kA ^ 64;
            const uint32_t qo = t * 16 + ((g >> 1) & 1) * 64 + (g & 1) * 8;
            const uint32_t v0 = slot + 16384 + (2 * t) * 128 + ((g ^ (2 * t)) << 4), v1 = (v0 + 128) ^ 16;
            const uint32_t sl0 = (g & 1) ? 0x1044u : 0x4410u, sl1 = (g & 1) ? 0x3244u : 0x4432u;
            const uint32_t sa0 = (g & 2) ? 0x4444u : sl0, sa1 = (g & 2) ? 0x4444u : sl1;
            const uint32_t sb0 = (g & 2) ? sl0 : 0x4444u, sb1 = (g & 2) ? sl1 : 0x4444u;
            const int d0 = 64 * (t >> 1) + 8 * g + 4 * (t & 1);
            uint32_t ph = 0;
            while (true) {
                const uint32_t qa = sb + SM_QA + (tk >> 7) * 256 + qo;
                bool vout = false;
                if (XRV && lane == 0 && tk >= NT - XRV && !mbar_wait_for(bar, ph, TV)) {
                    mbar_expect_tx(barV, 16384);
                    tma_3d(slot + 16384, &M.m_v, tk * 64, 0, barV, pol);
                    vout = true;
                }
                if (XRV) __syncwarp();
                mbar_wait(bar, ph);
                LAND(lane == 0, tk);
                unsigned nxt = 0;
                if (lane == 0) {
                    if (!vout) {
                        mbar_expect_tx(barV, 16384);
                        tma_3d(slot + 16384, &M.m_v, tk * 64, 0, barV, pol);
                    }
                    asm volatile("atom.relaxed.gpu.global.inc.u32 %0, [%1], %2;" : "=r"(nxt) : "l"(&G.ticket.v), "r"(DRAWS - 1) : "memory");
                }
                __syncwarp();
                mbar_wait(sb + SM_BAR + BAR_Q + (tk >> 10) * 8, 0);
                STAMP(tid == 128 && tk < NSTATIC, 3);
                uint2 qf[4];
                qf[0] = lds64(qa); qf[1] = lds64(qa ^ 64); qf[2] = lds64(qa + 128); qf[3] = lds64((qa ^ 64) + 128);
                float c[8][4];
#pragma unroll
                for (int i = 0; i < 32; i++) (&c[0][0])[i] = 0.f;
#pragma unroll
                for (int s = 0; s < 4; s++)
#pragma unroll
                    for (int jj = 0; jj < 8; jj++) {
                        const uint4 u = lds128(((s & 1) ? kB : kA) + jj * 2048 + (s >> 1) * 128);
                        mma16816(c[jj], u.x, u.y, u.z, u.w, qf[s].x, qf[s].y);
                    }
                float sc[8];
#pragma unroll
                for (int jj = 0; jj < 8; jj++) sc[jj] = c[jj][0] + c[jj][3];
#pragma unroll
                for (int jj = 0; jj < 8; jj += 2) scale_scores(sc[jj], sc[jj + 1]);
                float m = fmaxf(fmaxf(fmaxf(sc[0], sc[1]), fmaxf(sc[2], sc[3])), fmaxf(fmaxf(sc[4], sc[5]), fmaxf(sc[6], sc[7])));
                m = fmaxf(m, __shfl_xor_sync(~0u, m, 5));
                m = fmaxf(m, __shfl_xor_sync(~0u, m, 8));
                m = fmaxf(m, __shfl_xor_sync(~0u, m, 16));
                const float ms = __uint_as_float(tagw(m * LOG2E, tag));
                uint32_t W0[4], W1[4];
                float l = 0.f;
#pragma unroll
                for (int i = 0; i < 4; i++) {
                    const uint32_t pp = pack_bf16(ex2(fmaf(sc[2 * i], LOG2E, -ms)), ex2(fmaf(sc[2 * i + 1], LOG2E, -ms)));
                    W0[i] = __shfl_sync(~0u, pp, 8 * t);
                    W1[i] = __shfl_sync(~0u, pp, 8 * t + 5);
                    l += bf_lo(pp) + bf_hi(pp);
                }
                l += __shfl_xor_sync(~0u, l, 5);
                l += __shfl_xor_sync(~0u, l, 8);
                l += __shfl_xor_sync(~0u, l, 16);
                if (lane == 0 || lane == 2)
                    st_relaxed128((char*)G.partML + tk * 32 + lane * 8, __float_as_uint(ms), tagw(l, tag), __float_as_uint(ms), tagw(l, tag));
                uint32_t pb[16][2];
#pragma unroll
                for (int i = 0; i < 16; i++) {
                    const uint32_t pw = (i & 1) ? W1[i >> 2] : W0[i >> 2];
                    pb[i][0] = prmt(pw, 0, (i & 2) ? sa1 : sa0);
                    pb[i][1] = prmt(pw, 0, (i & 2) ? sb1 : sb0);
                    asm volatile("" : "+r"(pb[i][0]), "+r"(pb[i][1]));
                }
                float* po = G.partO + (size_t)tk * 128 + d0;
                asm volatile("" : "+l"(po));
                if (lane == 0) note_draw(smem + SM_BAR + W_PROG, nxt, &G.clk.v, tag);
                nxt += NSTATIC;
                if (nxt >= NT - XPK && nxt < NT && lane == 0) {
                    mbar_expect_tx(bar, 16384);
                    bulk_load(slot, (const char*)P.K + (size_t)nxt * 16384, 16384, bar, pol);
                }
                mbar_wait(barV, ph);
                LAND(lane == 0, 8192 + tk);
                ph ^= 1;
                if (nxt < NT - XPK && lane == 0) {
                    mbar_expect_tx(bar, 16384);
                    bulk_load(slot, (const char*)P.K + (size_t)nxt * 16384, 16384, bar, pol);
                }
                __syncwarp();
                float acc[2][4][4];
#pragma unroll
                for (int i = 0; i < 32; i++) (&acc[0][0][0])[i] = 0.f;
#pragma unroll
                for (int jj = 0; jj < 8; jj++)
#pragma unroll
                    for (int e = 0; e < 2; e++)
#pragma unroll
                        for (int hh = 0; hh < 2; hh++) {
                            const uint4 u = lds128((e ? v1 : v0) + jj * 1024 + hh * 8192);
                            mma16816(acc[hh][(jj & 1) * 2 + e], u.x, u.y, u.z, u.w, pb[2 * jj + e][0], pb[2 * jj + e][1]);
                        }
                float r4[4];
#pragma unroll
                for (int i = 0; i < 4; i++) {
                    const float x0 = (acc[0][0][i] + acc[0][1][i]) + (acc[0][2][i] + acc[0][3][i]);
                    const float x1 = (acc[1][0][i] + acc[1][1][i]) + (acc[1][2][i] + acc[1][3][i]);
                    r4[i] = (t & 2) ? x1 : x0;
                }
                st_relaxed128(po, tagw(r4[0], tag), tagw(r4[1], tag), tagw(r4[2], tag), tagw(r4[3], tag));
                nxt = __shfl_sync(~0u, nxt, 0);
                if (nxt >= NT) break;
                tk = nxt;
            }
            STAMP(lane == 0, 16 + wi);
        }
    } else {
        float* red = (float*)(smem + SM_RED2);
        if (tid == 32) {
            const uint32_t ep0 = ld_relaxed32(&G.epoch.v);
            for (int e = 0; e < 8; e++) mbar_init(sb + SM_BAR + BAR_Q + e * 8, 1);
            for (int e = 1; e < 10; e++) mbar_init(sb + SM_BAR + BAR_W + e * 8, 1);
            mbar_init(sb + SM_BAR + BAR_BDONE, 1);
            mbar_init(sb + SM_BAR + BAR_PDONE, 1);
            mbar_init(sb + SM_BAR + BAR_QABS, 1);
            mbar_init(sb + SM_BAR + BAR_WFREE, 1);
            asm volatile("fence.mbarrier_init.release.cluster;" ::: "memory");
            asm volatile("st.volatile.shared.v4.u32 [%0], {%1, %2, %1, %1};" ::"r"(sb + SM_BAR + W_PROG), "r"(0), "r"(now_ns()) : "memory");
            *(volatile uint32_t*)(smem + SM_BAR + W_EPOCH) = ep0;
        } else if (tid == 64) {
            asm volatile("prefetch.tensormap [%0];" ::"l"(&M.m_v) : "memory");
            asm volatile("prefetch.tensormap [%0];" ::"l"(&M.m_wqB) : "memory");
            asm volatile("prefetch.tensormap [%0];" ::"l"(&M.m_wuk) : "memory");
        }
        __syncthreads();
        const uint32_t epoch = *(volatile uint32_t*)(smem + SM_BAR + W_EPOCH);
        const uint32_t tag = (epoch + 1) & 1;
        STAMP(tid == 0, 14);

        if (hasSlice) {
            const uint32_t nt = tag ^ 1;
            const int qoff = ((tid >> 5) & 1) * 4096 + 32 * j + (tid & 31);
            if (tid < 64) {
                st_relaxed32(G.qA + qoff, nt); st_relaxed32(G.qB + qoff, nt);
                if (tid < 32) {
                    st_relaxed32(G.o + 32 * j + tid, nt); st_relaxed32(G.o + 4096 + 32 * j + tid, nt);
                    st_relaxed32(G.ctx + 32 * j + tid, nt); st_relaxed32(G.ctx + 4096 + 32 * j + tid, nt);
                }
            }
            if (j == 0 && tid >= 96) st_relaxed32(&G.clk.v + lane, nt);
            if (tid >= 64 && tid < 72) st_relaxed32((uint32_t*)P.out + 8 * j + (tid - 64), 0);
            mbar_wait(sb + SM_BAR + BAR_W, 0);
            LAND(tid == 0, 17408 + 0 * 128 + j);
            if (tid == 96) {
                mbar_expect_tx(sb + SM_BAR + BAR_W + 8, 32768);
                issue_tall(sb + SM_WQB, &M.m_wqB, j * 32, 0, sb + SM_BAR + BAR_W + 8, pol);
            }
            __syncwarp();
            STAMP(tid == 0, 15);
            uint2 bf[16];
            tall_prep(bf, sb + SM_P, warp, g, t);
            gemv_tall(sb + SM_WQ, bf, (float*)(smem + SM_RED1), warp, g, t);
            tall_finish((float*)(smem + SM_RED1), G.qA + qoff, tid, tag, 0, h >= HCLR ? 32 : 64);
            STAMP(tid == 0, 1);
            tall_prep(bf, sb + SM_P + 2048, warp, g, t);
            mbar_wait(sb + SM_BAR + BAR_W + 8, 0);
            LAND(tid == 0, 17408 + 1 * 128 + j);
            if (tid == 96) {
                mbar_expect_tx(sb + SM_BAR + BAR_W + 16, 32768);
                tma_2d(sb + SM_WUK, &M.m_wuk, h * 128, qd * 128, sb + SM_BAR + BAR_W + 16, pol);
            }
            __syncwarp();
            gemv_tall(sb + SM_WQB, bf, red, warp, g, t);
            tall_finish(red, G.qB + qoff, tid, tag);
            if (tid == 96) mbar_arrive(sb + SM_BAR + BAR_WFREE);
            STAMP(tid == 0, 25);
            named_bar(1, 128);
            uint4 qf[4];
            {
                const float* qp = G.qB + ((g & 1) * 32 + h) * 128 + t * 8;
                uint4 v[8];
                unsigned it = 0;
                while (true) {
                    uint32_t bad = 0;
#pragma unroll
                    for (int i = 0; i < 8; i++) v[i] = ld_relaxed128(qp + (i >> 1) * 32 + (i & 1) * 4);
#pragma unroll
                    for (int i = 0; i < 8; i++) bad |= bad4(v[i], tag);
                    if (!__any_sync(~0u, bad & 1u)) break;
                    __nanosleep(100);
                    if (++it > SPIN_LIMIT) __trap();
                }
#pragma unroll
                for (int s = 0; s < 4; s++)
                    qf[s] = make_uint4(pack_bf16(__uint_as_float(v[2 * s].x), __uint_as_float(v[2 * s].y)),
                                       pack_bf16(__uint_as_float(v[2 * s].z), __uint_as_float(v[2 * s].w)),
                                       pack_bf16(__uint_as_float(v[2 * s + 1].x), __uint_as_float(v[2 * s + 1].y)),
                                       pack_bf16(__uint_as_float(v[2 * s + 1].z), __uint_as_float(v[2 * s + 1].w)));
            }
            mbar_wait(sb + SM_BAR + BAR_W + 16, 0);
            LAND(tid == 0, 17408 + 2 * 128 + j);
#pragma unroll
            for (int jj = 0; jj < 2; jj++) {
                float c[4] = {0.f, 0.f, 0.f, 0.f};
#pragma unroll
                for (int s = 0; s < 4; s++) {
                    const uint32_t a = sb + SM_WUK + (32 * warp + 16 * jj + g) * 256 + (t + 4 * s) * 16;
                    const uint4 u = lds128(a), v = lds128(a + 2048);
                    mma16816(c, u.x, v.x, u.y, v.y, qf[s].x, qf[s].y);
                    mma16816(c, u.z, v.z, u.w, v.w, qf[s].z, qf[s].w);
                }
                const float val = (t & 2) ? ((t & 1) ? c[3] : c[2]) : ((t & 1) ? c[1] : c[0]);
                const int cc = 128 * qd + 32 * warp + 16 * jj + g + ((t & 2) ? 8 : 0);
                const int off = (cc >> 6) * 2048 + h * 64 + ((((cc & 63) >> 3) ^ (h & 7)) << 3) + (cc & 7);
                G.qabs[(t & 1) * 16384 + off] = __float2bfloat16(val);
            }
            named_bar(1, 128);
            if (tid == 0) red_release(&G.cntQabs.v);
            STAMP(tid == 0, 4);
            if (h >= HCLR) {
#pragma unroll
                for (int k = 0; k < 8; k++)
                    st_relaxed128(G.partO + (size_t)((32 + h) * 128 + 16 * k + (tid >> 3)) * 128 + qd * 32 + (tid & 7) * 4, nt, nt, nt, nt);
                if (tid < 64) st_relaxed128((char*)G.partML + ((32 + h) * 128 + qd * 32) * 32 + tid * 16, nt, nt, nt, nt);
                __threadfence();
                tall_finish((float*)(smem + SM_RED1), G.qA + qoff, tid, tag, 32, 64);
            }
        }

        if (isB) {
            const int ib = cta - NA_CTA;
            float acc[8][16];
#pragma unroll
            for (int i = 0; i < 8; i++)
#pragma unroll
                for (int k = 0; k < 16; k++) acc[i][k] = 0.f;
            float mrun[8], lrun[8];
#pragma unroll
            for (int i = 0; i < 8; i++) { mrun[i] = -INFINITY; lrun[i] = 0.f; }
            const uint64_t dQ = make_desc(sb + SM_SLOT + 5 * 32768);
            const uint64_t dP = make_desc(sb + SM_P);
            const uint32_t pst = sb + SM_P + (((lane >> 4) * 8 + (lane & 7)) * 128) + (((2 * warp + ((lane >> 3) & 1)) ^ (lane & 7)) << 4);
            mbar_wait(sb + SM_BAR + BAR_QABS, 0);
            STAMP(tid == 0, 5);
            int s0 = 0; uint32_t ph0 = 0;
            for (int it = 0; it < 16; it++) {
                int s1 = s0 + 1; uint32_t ph1 = ph0;
                if (s1 == 5) { s1 = 0; ph1 ^= 1; }
                const uint64_t dA0 = make_desc(sb + SM_SLOT + s0 * 32768), dA1 = make_desc(sb + SM_SLOT + s1 * 32768);
                float S[16];
                mbar_wait(sb + SM_BAR + BAR_BFULL + s0 * 8, ph0);
                mbar_wait(sb + SM_BAR + BAR_BFULL + s1 * 8, ph1);
                wg_fence();
#pragma unroll
                for (int k = 0; k < 32; k++) {
                    const uint64_t da = ((k < 16) ? dA0 : dA1) + (uint64_t)((((k >> 2) & 3) * 8192 + (k & 3) * 32) >> 4);
                    const uint64_t db = dQ + (uint64_t)(((k >> 2) * 4096 + (k & 3) * 32) >> 4);
                    wgmma_n32<0>(S, da, db, k > 0);
                }
                wg_commit();
                wg_wait<0>();
#pragma unroll
                for (int i = 0; i < 16; i++) S[i] *= SCALE;
                float mx[8];
#pragma unroll
                for (int i = 0; i < 8; i++) {
                    mx[i] = fmaxf(S[4 * (i >> 1) + (i & 1)], S[4 * (i >> 1) + 2 + (i & 1)]);
                    mx[i] = fmaxf(mx[i], __shfl_xor_sync(~0u, mx[i], 4));
                    mx[i] = fmaxf(mx[i], __shfl_xor_sync(~0u, mx[i], 8));
                    mx[i] = fmaxf(mx[i], __shfl_xor_sync(~0u, mx[i], 16));
                }
                if (g == 0) {
#pragma unroll
                    for (int jb = 0; jb < 4; jb++)
                        *(float2*)(red + warp * 32 + 8 * jb + 2 * t) = make_float2(mx[2 * jb], mx[2 * jb + 1]);
                }
                named_bar(1, 128);
                float al[8];
                bool chg = false;
                uint32_t R[8];
#pragma unroll
                for (int jb = 0; jb < 4; jb++) {
                    float2 a = *(float2*)(red + 8 * jb + 2 * t), b = *(float2*)(red + 32 + 8 * jb + 2 * t);
                    float2 c = *(float2*)(red + 64 + 8 * jb + 2 * t), d = *(float2*)(red + 96 + 8 * jb + 2 * t);
                    const float n0 = fmaxf(mrun[2 * jb], fmaxf(fmaxf(a.x, b.x), fmaxf(c.x, d.x)) * LOG2E);
                    const float n1 = fmaxf(mrun[2 * jb + 1], fmaxf(fmaxf(a.y, b.y), fmaxf(c.y, d.y)) * LOG2E);
                    chg |= (n0 != mrun[2 * jb]) | (n1 != mrun[2 * jb + 1]);
                    al[2 * jb] = ex2(mrun[2 * jb] - n0);
                    al[2 * jb + 1] = ex2(mrun[2 * jb + 1] - n1);
                    mrun[2 * jb] = n0; mrun[2 * jb + 1] = n1;
                    R[2 * jb]     = pack_bf16(ex2(fmaf(S[4 * jb], LOG2E, -n0)), ex2(fmaf(S[4 * jb + 1], LOG2E, -n1)));
                    R[2 * jb + 1] = pack_bf16(ex2(fmaf(S[4 * jb + 2], LOG2E, -n0)), ex2(fmaf(S[4 * jb + 3], LOG2E, -n1)));
                    lrun[2 * jb]     = fmaf(lrun[2 * jb], al[2 * jb], bf_lo(R[2 * jb]) + bf_lo(R[2 * jb + 1]));
                    lrun[2 * jb + 1] = fmaf(lrun[2 * jb + 1], al[2 * jb + 1], bf_hi(R[2 * jb]) + bf_hi(R[2 * jb + 1]));
                }
                asm volatile("stmatrix.sync.aligned.m8n8.x4.trans.shared.b16 [%0], {%1,%2,%3,%4};"
                             ::"r"(pst), "r"(R[0]), "r"(R[1]), "r"(R[2]), "r"(R[3]) : "memory");
                asm volatile("stmatrix.sync.aligned.m8n8.x4.trans.shared.b16 [%0], {%1,%2,%3,%4};"
                             ::"r"(pst + 2048), "r"(R[4]), "r"(R[5]), "r"(R[6]), "r"(R[7]) : "memory");
                asm volatile("fence.proxy.async.shared::cta;" ::: "memory");
                if (__any_sync(~0u, chg)) {
#pragma unroll
                    for (int mt = 0; mt < 8; mt++)
#pragma unroll
                        for (int k = 0; k < 16; k++) acc[mt][k] *= al[2 * (k >> 2) + (k & 1)];
                }
                named_bar(1, 128);
                wg_fence();
#pragma unroll
                for (int mt = 0; mt < 4; mt++)
#pragma unroll
                    for (int kk = 0; kk < 4; kk++)
                        wgmma_n32<1>(acc[mt], dA0 + (uint64_t)((mt * 8192 + kk * 2048) >> 4), dP + (uint64_t)((kk * 32) >> 4), 1);
                wg_commit();
#pragma unroll
                for (int mt = 0; mt < 4; mt++)
#pragma unroll
                    for (int kk = 0; kk < 4; kk++)
                        wgmma_n32<1>(acc[4 + mt], dA1 + (uint64_t)((mt * 8192 + kk * 2048) >> 4), dP + (uint64_t)((kk * 32) >> 4), 1);
                wg_commit();
                wg_wait<1>();
                if (lane == 0) mbar_arrive(sb + SM_BAR + BAR_BEMPTY + s0 * 8);
                wg_wait<0>();
                if (lane == 0) mbar_arrive(sb + SM_BAR + BAR_BEMPTY + s1 * 8);
                s0 = s1 + 1; ph0 = ph1;
                if (s0 == 5) { s0 = 0; ph0 ^= 1; }
            }
#pragma unroll
            for (int i = 0; i < 8; i++) {
                lrun[i] += __shfl_xor_sync(~0u, lrun[i], 4);
                lrun[i] += __shfl_xor_sync(~0u, lrun[i], 8);
                lrun[i] += __shfl_xor_sync(~0u, lrun[i], 16);
            }
            if (g == 0) {
#pragma unroll
                for (int jb = 0; jb < 4; jb++) {
                    *(float2*)(red + 128 + warp * 32 + 8 * jb + 2 * t) = make_float2(lrun[2 * jb], lrun[2 * jb + 1]);
                    if (warp == 0) *(float2*)(red + 256 + 8 * jb + 2 * t) = make_float2(mrun[2 * jb], mrun[2 * jb + 1]);
                }
            }
            named_bar(1, 128);
            if (tid == 0) mbar_arrive(sb + SM_BAR + BAR_BDONE);
            if (tid < 32)
                G.bml[ib * 32 + tid] = make_float2(red[256 + tid], red[128 + tid] + red[160 + tid] + red[192 + tid] + red[224 + tid]);
            float* bp = G.bpart + (size_t)ib * 16384 + (2 * t) * 512 + 16 * warp + g;
#pragma unroll
            for (int mt = 0; mt < 8; mt++)
#pragma unroll
                for (int k = 0; k < 16; k++)
                    bp[(8 * (k >> 2) + (k & 1)) * 512 + 64 * mt + ((k >> 1) & 1) * 8] = acc[mt][k];
            named_bar(1, 128);
            if (tid == 0) red_release(&G.cntB.v);
            STAMP(tid == 0, 6);
        }

        if (hasSlice) {
            if (tid == 0) {
                wait_prog(smem + SM_BAR + W_PROG, TUV);
                wait_counter(&G.cntB.v, (epoch + 1) * NB_CTA, 500);
                if (cta == 0) st_relaxed32(&G.epoch.v, epoch + 1);
                asm volatile("prefetch.tensormap [%0];" ::"l"(&M.m_uv[late]) : "memory");
                asm volatile("prefetch.tensormap [%0];" ::"l"(&M.m_w[mat]) : "memory");
            }
            named_bar(1, 128);
            if (tid == 32) mbar_arrive(sb + SM_BAR + BAR_PDONE);
            STAMP(tid == 0, 7);
            {
                const int b = tid >> 6, cp = tid & 63;
                uint2 ml[8];
#pragma unroll
                for (int i = 0; i < 8; i++) ml[i] = ld_relaxed64(G.bml + (b * 8 + i) * 32 + h);
                uint4 pv[2][8];
#pragma unroll
                for (int i = 0; i < 16; i++)
                    pv[i >> 3][i & 7] = ld_relaxed128(G.bpart + (size_t)(b * 8 + (i & 7)) * 16384 + h * 512 + (i >> 3) * 256 + 4 * cp);
                float M = __uint_as_float(ml[0].x);
#pragma unroll
                for (int i = 1; i < 8; i++) M = fmaxf(M, __uint_as_float(ml[i].x));
                float L = 0.f, wgt[8];
#pragma unroll
                for (int i = 0; i < 8; i++) {
                    wgt[i] = ex2(__uint_as_float(ml[i].x) - M);
                    L = fmaf(wgt[i], __uint_as_float(ml[i].y), L);
                }
                const float inv = 1.f / L;
#pragma unroll
                for (int x = 0; x < 2; x++) {
                    float v0 = 0.f, v1 = 0.f, v2 = 0.f, v3 = 0.f;
#pragma unroll
                    for (int i = 0; i < 8; i++) {
                        v0 = fmaf(wgt[i], __uint_as_float(pv[x][i].x), v0);
                        v1 = fmaf(wgt[i], __uint_as_float(pv[x][i].y), v1);
                        v2 = fmaf(wgt[i], __uint_as_float(pv[x][i].z), v2);
                        v3 = fmaf(wgt[i], __uint_as_float(pv[x][i].w), v3);
                    }
                    *(uint2*)(smem + SM_P + b * 1024 + x * 512 + cp * 8) = make_uint2(pack_bf16(v0 * inv, v1 * inv), pack_bf16(v2 * inv, v3 * inv));
                }
            }
            STAMP(tid == 0, 8);
        }
        {
            named_bar(1, 128);
#pragma unroll 1
            for (uint64_t plan = j < 64 ? 0xF7351260ull : (j < 124 ? (late ? 0xF75314260ull : 0xF7514603ull) : (hasSlice ? 0xF753426ull : 0xF10ull));
                 plan != 0xF; plan >>= 4) {
                const int step = plan & 15;
                if ((step & 14) == 4) {
                    const int hh = rg + 8 * warp;
                    const uint32_t real = step & 1, both = real & (mat | (warp != 3));
                    if (both) wait_ticket(smem + SM_BAR + W_PROG, mat ? NT + YB : min((33 + hh) * 128 + LAGT, NT + YLATE) + YX);
                    __syncwarp();
                    const float* src = (mat ? G.ctx : G.o) + hh * 128 + lane * 4;
                    uint4 v[2];
                    v[0] = v[1] = make_uint4(tag, tag, tag, tag);
                    uint32_t bad0 = real, bad1 = both;
                    unsigned it = 0;
                    while (true) {
                        ld_relaxed128_if(v[0], src, bad0);
                        ld_relaxed128_if(v[1], src + 4096, bad1);
                        bad0 = bad4(v[0], tag) & 1u; bad1 = bad4(v[1], tag) & 1u;
                        if (!__any_sync(~0u, bad0 | bad1)) break;
                        if (++it > SPIN_LIMIT) __trap();
                    }
#pragma unroll
                    for (int b = 0; b < 2; b++)
                        *(uint2*)(smem + SM_VEC + V_X + b * XSTR + (128 * warp + 4 * lane) * 2) =
                            make_uint2(pack_bf16(__uint_as_float(v[b].x), __uint_as_float(v[b].y)), pack_bf16(__uint_as_float(v[b].z), __uint_as_float(v[b].w)));
                    named_bar(1, 128);
                    STAMP(tid == 0, 29);
                } else if (step >= 6) {
                    const uint32_t real = step & 1;
                    const uint32_t xa = sb + SM_VEC + V_X + ((lane >> 1) & 1) * XSTR + 8 * (lane >> 3) * 2;
                    const uint32_t wa = sb + SM_SQ + 2 * 16384 + (8 * (lane >> 4) + (lane & 7)) * 128 +
                                        (((2 * warp + ((lane >> 3) & 1)) ^ (lane & 7)) << 4);
                    const uint32_t bs = sb + SM_BAR + BAR_S + 16;
                    const float* src = G.o + 4096 + (24 + rg) * 128 + lane * 4;
                    const uint32_t needx = real & (mat ^ 1);
                    uint32_t* dst = (uint32_t*)P.out + (t & 1) * 512 + mat * 256 + cg * 32 + warp * 8 + (t >> 1) * 4 + (g >> 1);
                    asm volatile("" : "+l"(dst));
                    uint4 v = make_uint4(tag, tag, tag, tag);
                    float d[4][4];
#pragma unroll
                    for (int i = 0; i < 16; i++) (&d[0][0])[i] = 0.f;
#pragma unroll 1
                    for (int u = 0; u < 3; u++) {
                        uint4 xf[4];
                        if (needx && u == 2) wait_ticket(smem + SM_BAR + W_PROG, NT + YP);
                        __syncwarp();
                        ld_relaxed128_if(v, src, needx & (u == 2));
#pragma unroll
                        for (int i = 0; i < 4; i++) xf[i] = ldsm4(xa + u * 256 + i * 64);
                        if (real) mbar_wait_nt(bs + u * 8, 0);
#pragma unroll
                        for (int i = 0; i < 4; i++) {
                            const uint4 w0 = ldsm4t(wa + u * 16384 + i * 4096), w1 = ldsm4t(wa + u * 16384 + i * 4096 + 2048);
                            mma16816(d[(i & 1) * 2], w0.x, w0.y, w0.z, w0.w, xf[i].x, xf[i].y);
                            mma16816(d[(i & 1) * 2 + 1], w1.x, w1.y, w1.z, w1.w, xf[i].z, xf[i].w);
                        }
                    }
                    unsigned it = 0;
                    while (__any_sync(~0u, bad4(v, tag) & 1u)) {
                        if (++it > SPIN_LIMIT) __trap();
                        v = ld_relaxed128(src);
                    }
                    STAMP(tid == 96, 20);
                    if (!mat)
                        *(uint2*)(smem + SM_VEC + V_X + XSTR + (384 + 4 * lane) * 2) =
                            make_uint2(pack_bf16(__uint_as_float(v.x), __uint_as_float(v.y)), pack_bf16(__uint_as_float(v.z), __uint_as_float(v.w)));
                    __syncwarp();
                    uint4 xf[4], w[4];
#pragma unroll
                    for (int i = 0; i < 4; i++) xf[i] = ldsm4(xa + 3 * 256 + i * 64);
#pragma unroll
                    for (int q = 0; q < 2; q++) {
                        if (q) {
#pragma unroll
                            for (int i = 0; i < 4; i++) {
                                d[0][i] = (d[0][i] + d[1][i]) + (d[2][i] + d[3][i]);
                                d[1][i] = d[2][i] = d[3][i] = 0.f;
                            }
                        }
                        if (real) mbar_wait_nt(bs + 24 + q * 8, 0);
#pragma unroll
                        for (int i = 0; i < 4; i++) w[i] = ldsm4t(wa + 3 * 16384 + q * 8192 + i * 2048);
#pragma unroll
                        for (int i = 0; i < 2; i++) {
                            mma16816(d[2 * i], w[2 * i].x, w[2 * i].y, w[2 * i].z, w[2 * i].w, xf[2 * q + i].x, xf[2 * q + i].y);
                            mma16816(d[2 * i + 1], w[2 * i + 1].x, w[2 * i + 1].y, w[2 * i + 1].z, w[2 * i + 1].w, xf[2 * q + i].z, xf[2 * q + i].w);
                        }
                    }
                    STAMP(tid == 64, 22);
                    float e[4];
#pragma unroll
                    for (int i = 0; i < 4; i++) e[i] = (t & 2) ? d[i][2] : d[i][0];
                    red_out(dst, ((e[0] + e[1]) + e[2]) + e[3], g, real);
                    STAMP(tid == 64, 13);
                    if (real) asm volatile("exit;");
                } else if (step >= 2) {
                    uint2 bf[16];
                    tall_prep(bf, sb + SM_P, warp, g, t);
                    if (step & 1) mbar_wait(sb + SM_BAR + BAR_S + (warp >> 1) * 8, 0);
                    LAND(tid == 64, 17408 + 3 * 128 + j);
                    gemv_tall(sb + SM_SQ, bf, red + 512, warp, g, t);
                    tall_finish(red + 512, G.ctx + ((tid >> 5) & 1) * 4096 + 32 * j + (tid & 31), tid, tag, 0, (step & 1) ? 64 : 0);
                    STAMP(tid == 0, 12);
                } else {
                    const int b = step;
                    const int hm = min(h, 31), bh = 32 * b + hm;
                    wait_ticket(smem + SM_BAR + W_PROG, min((bh + 1) * 128 + LAGT, NT + YLATE + max(hm - 27, 0) * YSL));
                    __syncwarp();
                    float* rb = red + b * 256;
                    combineA(G, bh, qd, tag, rb, tid, smem + SM_BAR + W_PROG);
                    {
                        if (tid < 32)
                            st_relaxed32(G.o + bh * 128 + 32 * qd + tid, tagw((rb[tid] + rb[32 + tid]) + (rb[64 + tid] + rb[96 + tid]), tag));
                        STAMP(tid == 0, 9 + 2 * b);
                    }
                }
            }
        }
    }
}

typedef CUresult (*EncodeFn)(CUtensorMap*, CUtensorMapDataType, cuuint32_t, void*, const cuuint64_t*, const cuuint64_t*,
                             const cuuint32_t*, const cuuint32_t*, CUtensorMapInterleave, CUtensorMapSwizzle,
                             CUtensorMapL2promotion, CUtensorMapFloatOOBfill);

}

extern "C" void kernel_launch(void* const* d_in, const int* in_sizes, int n_in, void* d_out, int out_size) {
    (void)in_sizes; (void)n_in; (void)out_size;
    static EncodeFn encode = nullptr;
    static void* scratch = nullptr;
    if (!encode) {
        void* fn = nullptr;
        cudaDriverEntryPointQueryResult st;
        cudaGetDriverEntryPoint("cuTensorMapEncodeTiled", &fn, cudaEnableDefault, &st);
        encode = (EncodeFn)fn;
        cudaGetSymbolAddress(&scratch, g_raw);
        cudaFuncSetAttribute(fused_decode_kernel, cudaFuncAttributeMaxDynamicSharedMemorySize, SM_TOTAL);
    }
    Ptrs P;
    Maps M;
    auto mk = [&](CUtensorMap* m, void* ptr, cuuint64_t cols, cuuint64_t rows, cuuint32_t bc, cuuint32_t br, CUtensorMapSwizzle sw,
                  CUtensorMapL2promotion promo) {
        const cuuint64_t gdim[2] = {cols, rows};
        const cuuint64_t gstr[1] = {cols * 2};
        const cuuint32_t box[2] = {bc, br};
        const cuuint32_t estr[2] = {1, 1};
        encode(m, CU_TENSOR_MAP_DATA_TYPE_BFLOAT16, 2, ptr, gdim, gstr, box, estr, CU_TENSOR_MAP_INTERLEAVE_NONE, sw,
               promo, CU_TENSOR_MAP_FLOAT_OOB_FILL_NONE);
    };
    mk(&M.m_wq, d_in[3], 4096, 512, 32, 256, CU_TENSOR_MAP_SWIZZLE_64B, CU_TENSOR_MAP_L2_PROMOTION_NONE);
    auto mk3 = [&](CUtensorMap* m, void* ptr, cuuint64_t cols, cuuint64_t rows) {
        const cuuint64_t gdim[3] = {64, rows, cols / 64};
        const cuuint64_t gstr[2] = {cols * 2, 128};
        const cuuint32_t box[3] = {64, 64, 2};
        const cuuint32_t estr[3] = {1, 1, 1};
        encode(m, CU_TENSOR_MAP_DATA_TYPE_BFLOAT16, 3, ptr, gdim, gstr, box, estr, CU_TENSOR_MAP_INTERLEAVE_NONE,
               CU_TENSOR_MAP_SWIZZLE_128B, CU_TENSOR_MAP_L2_PROMOTION_L2_256B, CU_TENSOR_MAP_FLOAT_OOB_FILL_NONE);
    };
    mk3(&M.m_v, d_in[2], 128, 524288);
    mk(&M.m_uv[0], d_in[9], 4096, 512, 32, 128, CU_TENSOR_MAP_SWIZZLE_64B, CU_TENSOR_MAP_L2_PROMOTION_NONE);
    mk(&M.m_uv[1], d_in[9], 4096, 512, 32, 128, CU_TENSOR_MAP_SWIZZLE_64B, CU_TENSOR_MAP_L2_PROMOTION_L2_256B);
    mk(&M.m_w[0], d_in[4], 512, 4096, 64, 64, CU_TENSOR_MAP_SWIZZLE_128B, CU_TENSOR_MAP_L2_PROMOTION_L2_256B);
    mk(&M.m_w[1], d_in[10], 512, 4096, 64, 64, CU_TENSOR_MAP_SWIZZLE_128B, CU_TENSOR_MAP_L2_PROMOTION_L2_256B);
    mk(&M.m_ckv, d_in[6], 512, 16384, 64, 64, CU_TENSOR_MAP_SWIZZLE_128B, CU_TENSOR_MAP_L2_PROMOTION_L2_256B);
    mk(&M.m_wqB, d_in[7], 4096, 512, 32, 256, CU_TENSOR_MAP_SWIZZLE_64B, CU_TENSOR_MAP_L2_PROMOTION_NONE);
    mk(&M.m_wuk, d_in[8], 4096, 512, 128, 128, CU_TENSOR_MAP_SWIZZLE_NONE, CU_TENSOR_MAP_L2_PROMOTION_L2_256B);
    P.xA = (const __nv_bfloat16*)d_in[0];
    P.K = (const __nv_bfloat16*)d_in[1];
    P.xB = (const __nv_bfloat16*)d_in[5];
    P.out = (__nv_bfloat16*)d_out;
    P.g = (Scratch*)scratch;
    cudaLaunchConfig_t cfg = {};
    cfg.gridDim = dim3(GRID);
    cfg.blockDim = dim3(NTHREADS);
    cfg.dynamicSmemBytes = SM_TOTAL;
    cfg.stream = cudaStreamPerThread;
    cudaLaunchAttribute attr;
    attr.id = cudaLaunchAttributeCooperative;
    attr.val.cooperative = 1;
    cfg.attrs = &attr;
    cfg.numAttrs = 1;
    cudaLaunchKernelEx(&cfg, fused_decode_kernel, P, M);
}
```

```cpp
#include <cuda_runtime.h>
#include <cuda_bf16.h>
#include <cuda.h>
#include <stdint.h>

namespace {

constexpr int NT       = 8192;
constexpr int GRID     = 132;
constexpr int NB_CTA   = 16;
constexpr int NA_CTA   = GRID - NB_CTA;
constexpr int NWORK    = 3;
#define YV 292
#define DV 54
#define YW 407
#define DW 68
#define DL 6
#define YX 150
#define YB 582
#define YP 605
#define XRV 330
#define TV 3200
#define PFB 16384
#define LAGT 1060
#define YLATE 120
#define YSL 70
#define YO 450
#define YOS 40
#define TUV (43 * 128)
#define XPK 80
#define FRZ 300
#define GLOOK 120
#define QDELAY 850
constexpr int NEARX = 400;
constexpr int GN = 8, GST = 16;
constexpr int JE0   = 112;
constexpr int HCLR  = 26;
constexpr int BINFL = 2;
constexpr int NSTATIC  = NA_CTA * NWORK;
constexpr unsigned DRAWS = (NT - NSTATIC) + GRID * NWORK;
static_assert(52 * 128 + LAGT + 300 <= NT && TUV + 10 * 128 <= NT, "wait_prog thresholds must be reachable");
constexpr int NTHREADS = 256;
constexpr float SCALE = 0.08838834764831845f, LOG2E = 1.4426950408889634f;
constexpr unsigned SPIN_LIMIT = 1u << 22;

constexpr int SM_SLOT  = 0;
constexpr int SM_QA    = 196608;
constexpr int SM_P     = SM_QA + 16384;
constexpr int SM_RED1  = SM_P + 4096;
constexpr int SM_RED2  = SM_RED1 + 2048;
constexpr int SM_VEC   = SM_RED2 + 4096;
constexpr int SM_BAR   = SM_VEC + 3072;
constexpr int SM_TOTAL = SM_BAR + 352;
constexpr int V_X    = 512;
constexpr int BAR_FULL = 0;
constexpr int BAR_PDONE= 48;
constexpr int BAR_BDONE= 56;
constexpr int BAR_QABS = 72;
constexpr int BAR_BFULL= 80;
constexpr int BAR_BEMPTY=120;
constexpr int BAR_WFREE= 160;
constexpr int BAR_W    = 168;
constexpr int BAR_S    = 192;
constexpr int BAR_Q    = 264;
constexpr int W_EPOCH  = 328;
constexpr int W_PROG   = 336;
constexpr int SM_WQ = 3 * 32768, SM_WQB = 4 * 32768, SM_WUK = 5 * 32768;
constexpr int SM_SQ = 3 * 32768;
constexpr int XSTR = 1024 + 16;

struct __align__(128) Cnt { unsigned v; unsigned pad[31]; };
struct __align__(128) Scratch {
    Cnt epoch, ticket, cntQabs, cntB;
    float qA[64 * 128], qB[64 * 128];
    __nv_bfloat16 qabs[2 * 32 * 512];
    float  partO[NT * 128];
    float2 partML[NT * 4];
    float  bpart[NB_CTA * 32 * 512];
    float2 bml[NB_CTA * 32];
    float  ctx[32 * 4 * 2 * 128];
    float  o[2 * 4096];
    Cnt    clk;
};
__device__ __align__(128) unsigned char g_raw[sizeof(Scratch)];

__device__ __forceinline__ int slice_of(int cta) {
    return cta >= 128 ? cta : ((cta & 8) << 3) | ((cta >> 4) << 3) | (cta & 7);
}

#define STAMP(cond, i) do {} while (0)
#define LAND(cond, i) do {} while (0)

__device__ __forceinline__ void mbar_init(uint32_t bar, int cnt) {
    asm volatile("mbarrier.init.shared::cta.b64 [%0], %1;" ::"r"(bar), "r"(cnt) : "memory");
}
__device__ __forceinline__ void mbar_expect_tx(uint32_t bar, uint32_t bytes) {
    asm volatile("mbarrier.arrive.expect_tx.shared::cta.b64 _, [%0], %1;" ::"r"(bar), "r"(bytes) : "memory");
}
__device__ __forceinline__ void mbar_arrive(uint32_t bar) {
    asm volatile("mbarrier.arrive.shared::cta.b64 _, [%0];" ::"r"(bar) : "memory");
}
__device__ __forceinline__ void mbar_wait(uint32_t bar, uint32_t parity) {
    unsigned it = 0;
    while (true) {
        uint32_t ok;
        asm volatile("{\n.reg .pred p;\nmbarrier.try_wait.parity.shared::cta.b64 p, [%1], %2;\nselp.u32 %0, 1, 0, p;\n}\n"
                     : "=r"(ok) : "r"(bar), "r"(parity) : "memory");
        if (ok) break;
        if (++it > SPIN_LIMIT) __trap();
    }
}
__device__ __forceinline__ void mbar_wait_nt(uint32_t bar, uint32_t parity) {
#pragma unroll 1
    for (unsigned it = 0; it < SPIN_LIMIT; it++) {
        uint32_t ok;
        asm volatile("{\n.reg .pred p;\nmbarrier.try_wait.parity.shared::cta.b64 p, [%1], %2;\nselp.u32 %0, 1, 0, p;\n}\n"
                     : "=r"(ok) : "r"(bar), "r"(parity) : "memory");
        if (ok) break;
    }
}
__device__ __forceinline__ bool mbar_test(uint32_t bar, uint32_t parity) {
    uint32_t ok;
    asm volatile("{\n.reg .pred p;\nmbarrier.test_wait.parity.shared::cta.b64 p, [%1], %2;\nselp.u32 %0, 1, 0, p;\n}\n"
                 : "=r"(ok) : "r"(bar), "r"(parity) : "memory");
    return ok;
}
__device__ __forceinline__ void bulk_load(uint32_t dst, const void* src, uint32_t bytes, uint32_t bar, uint64_t pol) {
    asm volatile("cp.async.bulk.shared::cluster.global.mbarrier::complete_tx::bytes.L2::cache_hint [%0], [%1], %2, [%3], %4;"
                 ::"r"(dst), "l"(src), "r"(bytes), "r"(bar), "l"(pol) : "memory");
}
__device__ __forceinline__ void bulk_load_nohint(uint32_t dst, const void* src, uint32_t bytes, uint32_t bar) {
    asm volatile("cp.async.bulk.shared::cluster.global.mbarrier::complete_tx::bytes [%0], [%1], %2, [%3];"
                 ::"r"(dst), "l"(src), "r"(bytes), "r"(bar) : "memory");
}
__device__ __forceinline__ void tma_2d(uint32_t dst, const CUtensorMap* map, int c0, int c1, uint32_t bar, uint64_t pol) {
    asm volatile("cp.async.bulk.tensor.2d.shared::cluster.global.mbarrier::complete_tx::bytes.L2::cache_hint [%0], [%1, {%3, %4}], [%2], %5;"
                 ::"r"(dst), "l"(map), "r"(bar), "r"(c0), "r"(c1), "l"(pol) : "memory");
}
__device__ __forceinline__ void tma_3d(uint32_t dst, const CUtensorMap* map, int c1, int c2, uint32_t bar, uint64_t pol) {
    asm volatile("cp.async.bulk.tensor.3d.shared::cluster.global.mbarrier::complete_tx::bytes.L2::cache_hint [%0], [%1, {%3, %4, %5}], [%2], %6;"
                 ::"r"(dst), "l"(map), "r"(bar), "r"(0), "r"(c1), "r"(c2), "l"(pol) : "memory");
}
__device__ __forceinline__ void wait_prog(const unsigned char* smem_word, unsigned th) {
    unsigned it = 0;
    while (*(volatile const unsigned*)(smem_word + 8) + NSTATIC < th) {
        __nanosleep(60);
        if (++it > SPIN_LIMIT) __trap();
    }
}
__device__ __forceinline__ uint32_t now_ns() {
    uint32_t t;
    asm volatile("mov.u32 %0, %globaltimer_lo;" : "=r"(t) :: "memory");
    return t;
}
__device__ __forceinline__ void note_draw(unsigned char* smem_word, unsigned raw, unsigned* clk, uint32_t tag) {
    const uint32_t a = (uint32_t)__cvta_generic_to_shared(smem_word);
    asm volatile("st.volatile.u32 [%0], %1;" ::"l"(smem_word + 8), "r"(raw) : "memory");
    const uint32_t now = now_ns();
    if ((int)raw < NT - NSTATIC - FRZ) asm volatile("st.volatile.shared.v2.u32 [%0], {%1, %2};" ::"r"(a), "r"(raw), "r"(now) : "memory");
    const unsigned q = NT - NSTATIC - FRZ - raw;
    if ((q & ~((GN - 1) * GST)) == 0)
        asm volatile("st.relaxed.gpu.global.u32 [%0], %1;" ::"l"(clk + q / GST), "r"(((now + q * 10) & ~1u) | tag) : "memory");
}
__device__ __forceinline__ void wait_ticket(const unsigned char* smem_word, int th) {
    wait_prog(smem_word, min(th, NT - NEARX));
    uint32_t tk, t0;
#pragma unroll 1
    for (unsigned it = 0; it < SPIN_LIMIT; it++) {
        asm volatile("ld.volatile.shared.v2.u32 {%0, %1}, [%2];" : "=r"(tk), "=r"(t0) : "r"((uint32_t)__cvta_generic_to_shared(smem_word)) : "memory");
        if ((int)(now_ns() - t0) >= (th - NSTATIC - (int)tk) * 10) break;
        __nanosleep(20);
    }
}
__device__ __forceinline__ bool mbar_wait_for(uint32_t bar, uint32_t parity, int n) {
    uint32_t c0, c;
    asm volatile("mov.u32 %0, %%clock;" : "=r"(c0) :: "memory");
    do {
        if (mbar_test(bar, parity)) return true;
        asm volatile("mov.u32 %0, %%clock;" : "=r"(c) :: "memory");
    } while ((int)(c - c0) < n);
    return false;
}
__device__ __forceinline__ bool elect_one() {
    uint32_t p;
    asm volatile("{\n.reg .pred p;\nelect.sync _|p, 0xffffffff;\nselp.u32 %0, 1, 0, p;\n}\n" : "=r"(p));
    return p;
}
__device__ __forceinline__ void fence_proxy_async() { asm volatile("fence.proxy.async;" ::: "memory"); }
__device__ __forceinline__ void named_bar(int id, int n) { asm volatile("bar.sync %0, %1;" ::"r"(id), "r"(n) : "memory"); }

__device__ __forceinline__ uint4 lds128(uint32_t a) {
    uint4 v;
    asm volatile("ld.shared.v4.u32 {%0,%1,%2,%3}, [%4];" : "=r"(v.x), "=r"(v.y), "=r"(v.z), "=r"(v.w) : "r"(a));
    return v;
}
__device__ __forceinline__ uint4 ldsm4(uint32_t a) {
    uint4 v;
    asm volatile("ldmatrix.sync.aligned.m8n8.x4.shared.b16 {%0,%1,%2,%3}, [%4];" : "=r"(v.x), "=r"(v.y), "=r"(v.z), "=r"(v.w) : "r"(a));
    return v;
}
__device__ __forceinline__ uint4 ldsm4t(uint32_t a) {
    uint4 v;
    asm volatile("ldmatrix.sync.aligned.m8n8.x4.trans.shared.b16 {%0,%1,%2,%3}, [%4];" : "=r"(v.x), "=r"(v.y), "=r"(v.z), "=r"(v.w) : "r"(a));
    return v;
}
__device__ __forceinline__ uint2 lds64(uint32_t a) {
    uint2 v;
    asm volatile("ld.shared.v2.u32 {%0,%1}, [%2];" : "=r"(v.x), "=r"(v.y) : "r"(a));
    return v;
}
__device__ __forceinline__ uint4 ld_relaxed128(const void* p) {
    uint4 v;
    asm volatile("ld.relaxed.gpu.global.v4.u32 {%0,%1,%2,%3}, [%4];" : "=r"(v.x), "=r"(v.y), "=r"(v.z), "=r"(v.w) : "l"(p) : "memory");
    return v;
}
__device__ __forceinline__ uint2 ld_relaxed64(const void* p) {
    uint2 v;
    asm volatile("ld.relaxed.gpu.global.v2.u32 {%0,%1}, [%2];" : "=r"(v.x), "=r"(v.y) : "l"(p) : "memory");
    return v;
}
__device__ __forceinline__ uint32_t ld_relaxed32(const void* p) {
    uint32_t v;
    asm volatile("ld.relaxed.gpu.global.u32 %0, [%1];" : "=r"(v) : "l"(p) : "memory");
    return v;
}
__device__ __forceinline__ uint32_t ld_acquire32(const void* p) {
    uint32_t v;
    asm volatile("ld.acquire.gpu.global.u32 %0, [%1];" : "=r"(v) : "l"(p) : "memory");
    return v;
}
__device__ __forceinline__ void st_relaxed128(void* p, uint32_t a, uint32_t b, uint32_t c, uint32_t d) {
    asm volatile("st.relaxed.gpu.global.v4.u32 [%0], {%1,%2,%3,%4};" ::"l"(p), "r"(a), "r"(b), "r"(c), "r"(d) : "memory");
}
__device__ __forceinline__ void red_release(unsigned* p) {
    asm volatile("red.release.gpu.global.add.u32 [%0], 1;" ::"l"(p) : "memory");
}
__device__ __forceinline__ void wait_counter(const unsigned* p, unsigned target, unsigned ns) {
    unsigned it = 0;
    while ((int)(ld_acquire32(p) - target) < 0) {
        __nanosleep(ns);
        if (++it > SPIN_LIMIT) __trap();
    }
}
__device__ __forceinline__ uint32_t prmt(uint32_t a, uint32_t b, uint32_t s) {
    uint32_t d;
    asm("prmt.b32 %0, %1, %2, %3;" : "=r"(d) : "r"(a), "r"(b), "r"(s));
    return d;
}
__device__ __forceinline__ uint32_t pack_bf16(float lo, float hi) {
    uint32_t d;
    asm("cvt.rn.bf16x2.f32 %0, %1, %2;" : "=r"(d) : "f"(hi), "f"(lo));
    return d;
}
__device__ __forceinline__ float ex2(float x) {
    float y;
    asm("ex2.approx.ftz.f32 %0, %1;" : "=f"(y) : "f"(x));
    return y;
}
__device__ __forceinline__ float bf_lo(uint32_t v) { return __uint_as_float(v << 16); }
__device__ __forceinline__ float bf_hi(uint32_t v) { return __uint_as_float(v & 0xffff0000u); }
__device__ __forceinline__ void scale_scores(float& a, float& b) {
    uint32_t p = pack_bf16(a, b);
    p = pack_bf16(bf_lo(p) * SCALE, bf_hi(p) * SCALE);
    a = bf_lo(p); b = bf_hi(p);
}
__device__ __forceinline__ uint32_t tagw(float v, uint32_t tag) {
    uint32_t d;
    asm("lop3.b32 %0, %1, 0xfffffffe, %2, 0xEA;" : "=r"(d) : "r"(__float_as_uint(v)), "r"(tag));
    return d;
}
__device__ __forceinline__ uint32_t bad2(uint32_t x, uint32_t y, uint32_t tag) {
    uint32_t d;
    asm("lop3.b32 %0, %1, %2, %3, 0x7E;" : "=r"(d) : "r"(x), "r"(y), "r"(tag));
    return d;
}
__device__ __forceinline__ uint32_t bad4(const uint4& v, uint32_t tag) { return bad2(v.x, v.y, tag) | bad2(v.z, v.w, tag); }
__device__ __forceinline__ void ld_relaxed128_if(uint4& v, const void* p, uint32_t c) {
    asm volatile("{\n.reg .pred p;\nsetp.ne.u32 p, %5, 0;\n@p ld.relaxed.gpu.global.v4.u32 {%0,%1,%2,%3}, [%4];\n}\n"
                 : "+r"(v.x), "+r"(v.y), "+r"(v.z), "+r"(v.w) : "l"(p), "r"(c) : "memory");
}
__device__ __forceinline__ void ld_relaxed64_if(uint2& v, const void* p, uint32_t c) {
    asm volatile("{\n.reg .pred p;\nsetp.ne.u32 p, %3, 0;\n@p ld.relaxed.gpu.global.v2.u32 {%0,%1}, [%2];\n}\n"
                 : "+r"(v.x), "+r"(v.y) : "l"(p), "r"(c) : "memory");
}
__device__ __forceinline__ void st_relaxed32(void* p, uint32_t a) {
    asm volatile("st.relaxed.gpu.global.u32 [%0], %1;" ::"l"(p), "r"(a) : "memory");
}
__device__ __forceinline__ void red_out(uint32_t* word, float v, int col, uint32_t go) {
    const uint32_t pk = (col & 1) ? pack_bf16(-0.f, v) : pack_bf16(v, -0.f);
    asm volatile("{\n.reg .pred p;\nsetp.ne.u32 p, %2, 0;\n@p red.relaxed.gpu.global.add.noftz.bf16x2 [%0], %1;\n}\n"
                 ::"l"(word), "r"(pk), "r"(go) : "memory");
}
__device__ __forceinline__ void mma16816(float (&c)[4], uint32_t a0, uint32_t a1, uint32_t a2, uint32_t a3,
                                         uint32_t b0, uint32_t b1) {
    asm("mma.sync.aligned.m16n8k16.row.col.f32.bf16.bf16.f32 {%0,%1,%2,%3}, {%4,%5,%6,%7}, {%8,%9}, {%0,%1,%2,%3};"
        : "+f"(c[0]), "+f"(c[1]), "+f"(c[2]), "+f"(c[3])
        : "r"(a0), "r"(a1), "r"(a2), "r"(a3), "r"(b0), "r"(b1));
}
__device__ __forceinline__ uint64_t make_desc(uint32_t addr) {
    return (uint64_t)((addr & 0x3FFFF) >> 4) | ((uint64_t)1 << 16) | ((uint64_t)64 << 32) | ((uint64_t)1 << 62);
}
template <int TRANS_A>
__device__ __forceinline__ void wgmma_n32(float (&d)[16], uint64_t da, uint64_t db, int scale_d) {
    asm volatile("{\n.reg .pred p;\nsetp.ne.b32 p, %18, 0;\n"
                 "wgmma.mma_async.sync.aligned.m64n32k16.f32.bf16.bf16 "
                 "{%0,%1,%2,%3,%4,%5,%6,%7,%8,%9,%10,%11,%12,%13,%14,%15}, %16, %17, p, 1, 1, %19, 0;\n}\n"
                 : "+f"(d[0]), "+f"(d[1]), "+f"(d[2]), "+f"(d[3]), "+f"(d[4]), "+f"(d[5]), "+f"(d[6]), "+f"(d[7]),
                   "+f"(d[8]), "+f"(d[9]), "+f"(d[10]), "+f"(d[11]), "+f"(d[12]), "+f"(d[13]), "+f"(d[14]), "+f"(d[15])
                 : "l"(da), "l"(db), "r"(scale_d), "n"(TRANS_A));
}
__device__ __forceinline__ void wg_fence()  { asm volatile("wgmma.fence.sync.aligned;" ::: "memory"); }
__device__ __forceinline__ void wg_commit() { asm volatile("wgmma.commit_group.sync.aligned;" ::: "memory"); }
template <int N> __device__ __forceinline__ void wg_wait() { asm volatile("wgmma.wait_group.sync.aligned %0;" ::"n"(N) : "memory"); }

__device__ __forceinline__ void issue_tall(uint32_t dst, const CUtensorMap* map, int col, int row, uint32_t bar, uint64_t pol) {
    tma_2d(dst, map, col, row, bar, pol);
    tma_2d(dst + 16384, map, col, row + 256, bar, pol);
}
__device__ __forceinline__ void tall_prep(uint2 (&bf)[16], uint32_t xbase, int w4, int g, int t) {
    const uint32_t xp = xbase + ((g >> 1) & 1) * 1024 + w4 * 256 + (t >> 1) * 8;
    const uint32_t sel = (g & 1) ? ((t & 1) ? 0x3244u : 0x1044u) : ((t & 1) ? 0x4432u : 0x4410u);
#pragma unroll
    for (int i = 0; i < 16; i++) {
        const uint2 xw = lds64(xp + i * 16);
        bf[i] = make_uint2(prmt(xw.x, 0, sel), prmt(xw.y, 0, sel));
    }
}
__device__ __forceinline__ void gemv_tall(uint32_t wbase, const uint2 (&bf)[16], float* red, int w4, int g, int t) {
    const uint32_t wu = wbase + (128 * w4 + (t & 1) + 4 * (t >> 1)) * 64 + (((g >> 1) ^ (t & 2)) << 4) + (g & 1) * 8;
    const uint32_t wv = (wu + 128) ^ 16;
    float a[4][4];
#pragma unroll
    for (int i = 0; i < 16; i++) (&a[0][0])[i] = 0.f;
#pragma unroll
    for (int i = 0; i < 16; i++) {
        const uint2 u = lds64(wu + i * 512), v = lds64(wv + i * 512);
        mma16816(a[i & 3], u.x, u.y, v.x, v.y, bf[i].x, bf[i].y);
    }
    if (t < 2)
        *(float4*)(red + (w4 * 2 + t) * 32 + 4 * g) =
            make_float4((a[0][0] + a[1][0]) + (a[2][0] + a[3][0]), (a[0][1] + a[1][1]) + (a[2][1] + a[3][1]),
                        (a[0][2] + a[1][2]) + (a[2][2] + a[3][2]), (a[0][3] + a[1][3]) + (a[2][3] + a[3][3]));
}
__device__ __forceinline__ void tall_finish(const float* red, float* dst, int tid, uint32_t tag, int lo = 0, int hi = 64) {
    named_bar(1, 128);
    if (tid >= lo && tid < hi) {
        st_relaxed32(dst, tagw((red[tid] + red[64 + tid]) + (red[128 + tid] + red[192 + tid]), tag));
    }
}

__device__ __forceinline__ void combineA(Scratch& G, int bh, int dq, uint32_t tag, float* red, int tid, const unsigned char* prog) {
    const int r = tid >> 3, c4 = tid & 7, w4 = tid >> 5, lane = tid & 31;
    const float2* ml = G.partML + (bh * 128 + r) * 4;
    const float* po = G.partO + (size_t)(bh * 128 + r) * 128 + dq * 32 + c4 * 4;
    uint2 m[8];
    uint4 o[8];
    uint32_t bad[8];
    STAMP(tid == 0 && bh >= 32, 28);
#pragma unroll
    for (int k = 0; k < 8; k++) m[k] = ld_relaxed64(ml + 64 * k);
#pragma unroll
    for (int k = 0; k < 8; k++) {
        o[k] = make_uint4(~tag, ~tag, ~tag, ~tag);
        ld_relaxed128_if(o[k], po + (size_t)k * 16 * 128, bh < 60);
    }
    unsigned it = 0;
    while (true) {
        uint32_t any = 0;
#pragma unroll
        for (int k = 0; k < 8; k++) { bad[k] = bad2(m[k].x, m[k].y, tag) & 1u; any |= bad[k]; }
        if (!__any_sync(~0u, any)) break;
#pragma unroll
        for (int k = 0; k < 8; k++) ld_relaxed64_if(m[k], ml + 64 * k, bad[k]);
        if (++it > SPIN_LIMIT) __trap();
    }
    STAMP(tid == 0 && bh >= 32, 30);
    STAMP(tid == 0 && bh >= 32, 19);
    float M = fmaxf(fmaxf(fmaxf(__uint_as_float(m[0].x), __uint_as_float(m[1].x)), fmaxf(__uint_as_float(m[2].x), __uint_as_float(m[3].x))),
                    fmaxf(fmaxf(__uint_as_float(m[4].x), __uint_as_float(m[5].x)), fmaxf(__uint_as_float(m[6].x), __uint_as_float(m[7].x))));
    M = fmaxf(M, __shfl_xor_sync(~0u, M, 8));
    M = fmaxf(M, __shfl_xor_sync(~0u, M, 16));
    float wgt[8], L = 0.f;
#pragma unroll
    for (int k = 0; k < 8; k++) {
        wgt[k] = ex2(__uint_as_float(m[k].x) - M);
        L = fmaf(wgt[k], __uint_as_float(m[k].y), L);
    }
    L += __shfl_xor_sync(~0u, L, 8);
    L += __shfl_xor_sync(~0u, L, 16);
    if (lane == 0) { red[128 + w4] = M; red[132 + w4] = L; }
    named_bar(1, 128);
    {
        const float4 Mw = *(float4*)(red + 128), Lw = *(float4*)(red + 132);
        const float Mx = fmaxf(fmaxf(Mw.x, Mw.y), fmaxf(Mw.z, Mw.w));
        const float Lt = (ex2(Mw.x - Mx) * Lw.x + ex2(Mw.y - Mx) * Lw.y) + (ex2(Mw.z - Mx) * Lw.z + ex2(Mw.w - Mx) * Lw.w);
        const float f = ex2(M - Mx) / Lt;
#pragma unroll
        for (int k = 0; k < 8; k++) wgt[k] *= f;
    }
    STAMP(tid == 0 && bh >= 32, 23);
    if (bh >= 60) wait_ticket(prog, NT + YO + (bh - 63) * YOS);
    while (true) {
        uint32_t any = 0;
#pragma unroll
        for (int k = 0; k < 8; k++) { bad[k] = bad4(o[k], tag) & 1u; any |= bad[k]; }
        if (!__any_sync(~0u, any)) break;
#pragma unroll
        for (int k = 0; k < 8; k++) ld_relaxed128_if(o[k], po + (size_t)k * 16 * 128, bad[k]);
        if (++it > SPIN_LIMIT) __trap();
    }
    STAMP(tid == 0 && bh >= 32, 31);
    float a0 = 0.f, a1 = 0.f, a2 = 0.f, a3 = 0.f, b0 = 0.f, b1 = 0.f, b2 = 0.f, b3 = 0.f;
#pragma unroll
    for (int k = 0; k < 8; k += 2) {
        a0 = fmaf(wgt[k], __uint_as_float(o[k].x), a0); b0 = fmaf(wgt[k + 1], __uint_as_float(o[k + 1].x), b0);
        a1 = fmaf(wgt[k], __uint_as_float(o[k].y), a1); b1 = fmaf(wgt[k + 1], __uint_as_float(o[k + 1].y), b1);
        a2 = fmaf(wgt[k], __uint_as_float(o[k].z), a2); b2 = fmaf(wgt[k + 1], __uint_as_float(o[k + 1].z), b2);
        a3 = fmaf(wgt[k], __uint_as_float(o[k].w), a3); b3 = fmaf(wgt[k + 1], __uint_as_float(o[k + 1].w), b3);
    }
    a0 += b0; a1 += b1; a2 += b2; a3 += b3;
#pragma unroll
    for (int s = 8; s <= 16; s <<= 1) {
        a0 += __shfl_xor_sync(~0u, a0, s);
        a1 += __shfl_xor_sync(~0u, a1, s);
        a2 += __shfl_xor_sync(~0u, a2, s);
        a3 += __shfl_xor_sync(~0u, a3, s);
    }
    if (lane < 8) *(float4*)(red + w4 * 32 + c4 * 4) = make_float4(a0, a1, a2, a3);
    named_bar(1, 128);
    STAMP(tid == 0 && bh >= 32, 24);
}

struct Ptrs {
    const __nv_bfloat16 *K, *xA, *xB;
    __nv_bfloat16* out;
    Scratch* g;
};
struct Maps { CUtensorMap m_wq, m_v, m_ckv, m_wqB, m_wuk, m_uv[2], m_w[2]; };

__global__ void __launch_bounds__(NTHREADS, 1)
fused_decode_kernel(const Ptrs P, const __grid_constant__ Maps M) {
    extern __shared__ __align__(1024) unsigned char smem[];
    const uint32_t sb = (uint32_t)__cvta_generic_to_shared(smem);
    uint64_t pol;
    asm("createpolicy.fractional.L2::evict_first.b64 %0, 1.0;" : "=l"(pol));
    asm volatile("{\n.reg .pred p;\nsetp.lt.u32 p, %3, 32;\n@p cp.async.bulk.prefetch.L2.global.L2::cache_hint [%0], %1, %2;\n}\n"
                 ::"l"((const char*)P.K + (blockIdx.x << 14)), "n"(PFB), "l"(pol), "r"(threadIdx.x) : "memory");
    if (threadIdx.x < 32 && elect_one()) {
        mbar_init(sb + SM_BAR + BAR_FULL, 1);
        mbar_init(sb + SM_BAR + BAR_FULL + 16, 1);
        mbar_init(sb + SM_BAR + BAR_W, 1);
        asm volatile("fence.mbarrier_init.release.cluster;" ::: "memory");
        if (blockIdx.x < NA_CTA) {
            mbar_expect_tx(sb + SM_BAR + BAR_FULL, 16384);
            bulk_load(sb + SM_SLOT, (const char*)P.K + (blockIdx.x << 14), 16384, sb + SM_BAR + BAR_FULL, pol);
        }
        if (blockIdx.x < 128) {
            mbar_expect_tx(sb + SM_BAR + BAR_W, 32768 + 4096);
            issue_tall(sb + SM_WQ, &M.m_wq, slice_of(blockIdx.x) * 32, 0, sb + SM_BAR + BAR_W, pol);
            bulk_load_nohint(sb + SM_P, P.xA, 2048, sb + SM_BAR + BAR_W);
            bulk_load_nohint(sb + SM_P + 2048, P.xB, 2048, sb + SM_BAR + BAR_W);
        }
        if (blockIdx.x < NA_CTA) {
            mbar_expect_tx(sb + SM_BAR + BAR_FULL + 16, 16384);
            bulk_load(sb + SM_SLOT + 32768, (const char*)P.K + ((blockIdx.x + NA_CTA) << 14), 16384, sb + SM_BAR + BAR_FULL + 16, pol);
        }
    }
    const int tid = threadIdx.x, warp = __shfl_sync(~0u, tid >> 5, 0), lane = tid & 31;
    const int g = lane >> 2, t = lane & 3;
    const int cta = blockIdx.x;
    Scratch& G = *P.g;
    const bool isB = cta >= NA_CTA;
    const bool hasSlice = cta < 128;
    const int j = slice_of(cta), h = j >> 2, qd = cta & 3;
    const int mat = j >> 6, cg = j & 7, rg = (j >> 3) & 7;
    const bool late = j < JE0 || j >= 124;
    STAMP(tid == 32, 0);
    if (warp == 7) {
        __syncthreads();
        const uint32_t epoch = *(volatile uint32_t*)(smem + SM_BAR + W_EPOCH);
        const uint32_t tag = (epoch + 1) & 1;
        if (!isB) { mbar_wait(sb + SM_BAR + BAR_W, 0); __nanosleep(QDELAY); }
#pragma unroll 1
        for (int i = 0; i < 8; i++) {
            if (i == 4 && !isB) wait_prog(smem + SM_BAR + W_PROG, 16 * 128);
            if (i == 0 && isB) { mbar_wait(sb + SM_BAR + BAR_QABS, 0); __nanosleep(8000); }
            uint4 v[8];
            uint32_t bad[8];
#pragma unroll
            for (int k = 0; k < 8; k++) { bad[k] = 1; v[k] = make_uint4(0, 0, 0, 0); }
            unsigned it = 0;
            while (true) {
#pragma unroll
                for (int k = 0; k < 8; k++) ld_relaxed128_if(v[k], G.qA + (8 * i + k) * 128 + lane * 4, bad[k]);
                uint32_t any = 0;
#pragma unroll
                for (int k = 0; k < 8; k++) { bad[k] = bad4(v[k], tag) & 1u; any |= bad[k]; }
                if (!__any_sync(~0u, any)) break;
                __nanosleep(40);
                if (++it > SPIN_LIMIT) __trap();
            }
#pragma unroll
            for (int k = 0; k < 8; k++) {
                uint32_t* dst = (uint32_t*)(smem + SM_QA + (8 * i + k) * 256 + (lane >> 1) * 16 + (lane & 1) * 4);
                dst[0] = pack_bf16(__uint_as_float(v[k].x), __uint_as_float(v[k].y));
                dst[2] = pack_bf16(__uint_as_float(v[k].z), __uint_as_float(v[k].w));
            }
            __syncwarp();
            if (lane == 0) mbar_arrive(sb + SM_BAR + BAR_Q + i * 8);
            STAMP(lane == 0 && i == 0, 2);
        }
        STAMP(lane == 0, 21);
        if (hasSlice) mbar_wait(sb + SM_BAR + BAR_PDONE, 0);
#pragma unroll 1
        for (int p = 0; p < 12; p++) {
            const bool uv = p < 4;
            if (p == (late ? 0 : 4)) {
                wait_ticket(smem + SM_BAR + W_PROG, NT - FRZ + GLOOK);
                uint32_t v;
                unsigned it = 0;
                while (true) {
                    v = ld_relaxed32(&G.clk.v + (lane & (GN - 1)));
                    if (!__any_sync(~0u, (v ^ tag) & 1u)) break;
                    __nanosleep(200);
                    if (++it > SPIN_LIMIT) __trap();
                }
                const uint32_t v0 = __shfl_sync(~0u, v, 0);
                v = v0 + (__reduce_add_sync(~0u, (int)(v - v0)) >> 5);
                if (lane == 0)
                    asm volatile("st.volatile.shared.v2.u32 [%0], {%1, %2};" ::"r"(sb + SM_BAR + W_PROG), "r"(NT - NSTATIC - FRZ), "r"(v) : "memory");
                __syncwarp();
                if (!hasSlice) break;
            }
            if (lane == 0) {
                const int r = uv ? p * 128 : (p - 4) * 64;
                if (!uv || late)
                    wait_ticket(smem + SM_BAR + W_PROG, NT + (uv ? YV + (p * DV >> 1) : YW + ((p - 4) * DW >> 1) + (p == 11 ? DL : 0)));
                STAMP(p == 4, 10);
                const uint32_t bar = sb + SM_BAR + BAR_S + (p < 11 ? p >> 1 : 6) * 8;
                if (!(p & 1) || p == 11) mbar_expect_tx(bar, p < 10 ? 16384 : 8192);
                tma_2d(sb + SM_SQ + p * 8192, uv ? &M.m_uv[late] : &M.m_w[mat], uv ? j * 32 : cg * 64,
                       uv ? r : (rg + 8 * (r >> 7)) * 128 + (r & 127), bar, pol);
            }
            __syncwarp();
        }
    } else if (warp >= 4) {
        const int wi = warp - 4;
        const uint32_t slot = sb + SM_SLOT + wi * 32768;
        const uint32_t bar = sb + SM_BAR + BAR_FULL + wi * 16, barV = bar + 8;
        unsigned tk = wi * NA_CTA + cta;
        const bool ev = wi == 2;
        if (lane == 0) {
            if (ev) mbar_init(bar, 1);
            mbar_init(barV, 1);
            if (isB && wi == 0) {
                for (int s = 0; s < 5; s++) {
                    mbar_init(sb + SM_BAR + BAR_BFULL + s * 8, 1);
                    mbar_init(sb + SM_BAR + BAR_BEMPTY + s * 8, 4);
                }
            }
            asm volatile("fence.mbarrier_init.release.cluster;" ::: "memory");
        }
        __syncthreads();
        const uint32_t epoch = *(volatile uint32_t*)(smem + SM_BAR + W_EPOCH);
        const uint32_t tag = (epoch + 1) & 1;

        bool active = true;
        if (isB) {
            if (wi == 1 && lane == 0) {
                wait_counter(&G.cntQabs.v, (epoch + 1) * 128, 64);
                fence_proxy_async();
                mbar_expect_tx(sb + SM_BAR + BAR_QABS, 32768);
                bulk_load_nohint(sb + SM_SLOT + 5 * 32768, G.qabs + ((cta - NA_CTA) >> 3) * 16384, 32768, sb + SM_BAR + BAR_QABS);
            }
            if (wi == 0 && lane == 0) {
                const int ib = cta - NA_CTA;
                int s = 0, sl = 0; uint32_t ph = 1, phl = 0;
                for (int u = 0; u < 32; u++) {
                    if (u >= BINFL) {
                        mbar_wait(sb + SM_BAR + BAR_BFULL + sl * 8, phl);
                        LAND(true, 16384 + ib * 32 + u);
                        if (++sl == 5) { sl = 0; phl ^= 1; }
                    }
                    if (u == 3 && hasSlice) mbar_wait(sb + SM_BAR + BAR_WFREE, 0);
                    mbar_wait(sb + SM_BAR + BAR_BEMPTY + s * 8, ph);
                    const uint32_t fb = sb + SM_BAR + BAR_BFULL + s * 8;
                    const int row = (ib >> 3) * 8192 + ((u >> 1) * 8 + (ib & 7)) * 64;
                    mbar_expect_tx(fb, 32768);
                    for (int x = 0; x < 4; x++)
                        tma_2d(sb + SM_SLOT + s * 32768 + x * 8192, &M.m_ckv, ((u & 1) * 4 + x) * 64, row, fb, pol);
                    if (++s == 5) { s = 0; ph ^= 1; }
                }
            }
            __syncwarp();
            mbar_wait(sb + SM_BAR + BAR_BDONE, 0);
            if (lane == 0) {
                tk = atomicInc(&G.ticket.v, DRAWS - 1);
                note_draw(smem + SM_BAR + W_PROG, tk, &G.clk.v, tag);
                tk += NSTATIC;
            }
            tk = __shfl_sync(~0u, tk, 0);
            active = tk < NT;
        } else if (ev) {
            __syncwarp();
            mbar_wait(sb + SM_BAR + BAR_W + 8, 0);
        }
        if (active) {
            if ((isB || ev) && lane == 0) {
                mbar_expect_tx(bar, 16384);
                bulk_load(slot, (const char*)P.K + (size_t)tk * 16384, 16384, bar, pol);
            }
            const uint32_t kA = slot + g * 256 + t * 16 + (g & 1) * 64, kB = kA ^ 64;
            const uint32_t qo = t * 16 + ((g >> 1) & 1) * 64 + (g & 1) * 8;
            const uint32_t v0 = slot + 16384 + (2 * t) * 128 + ((g ^ (2 * t)) << 4), v1 = (v0 + 128) ^ 16;
            const uint32_t sl0 = (g & 1) ? 0x1044u : 0x4410u, sl1 = (g & 1) ? 0x3244u : 0x4432u;
            const uint32_t sa0 = (g & 2) ? 0x4444u : sl0, sa1 = (g & 2) ? 0x4444u : sl1;
            const uint32_t sb0 = (g & 2) ? sl0 : 0x4444u, sb1 = (g & 2) ? sl1 : 0x4444u;
            const int d0 = 64 * (t >> 1) + 8 * g + 4 * (t & 1);
            uint32_t ph = 0;
            while (true) {
                const uint32_t qa = sb + SM_QA + (tk >> 7) * 256 + qo;
                bool vout = false;
                if (XRV && lane == 0 && tk >= NT - XRV && !mbar_wait_for(bar, ph, TV)) {
                    mbar_expect_tx(barV, 16384);
                    tma_3d(slot + 16384, &M.m_v, tk * 64, 0, barV, pol);
                    vout = true;
                }
                if (XRV) __syncwarp();
                mbar_wait(bar, ph);
                LAND(lane == 0, tk);
                unsigned nxt = 0;
                if (lane == 0) {
                    if (!vout) {
                        mbar_expect_tx(barV, 16384);
                        tma_3d(slot + 16384, &M.m_v, tk * 64, 0, barV, pol);
                    }
                    asm volatile("atom.relaxed.gpu.global.inc.u32 %0, [%1], %2;" : "=r"(nxt) : "l"(&G.ticket.v), "r"(DRAWS - 1) : "memory");
                }
                __syncwarp();
                mbar_wait(sb + SM_BAR + BAR_Q + (tk >> 10) * 8, 0);
                STAMP(tid == 128 && tk < NSTATIC, 3);
                uint2 qf[4];
                qf[0] = lds64(qa); qf[1] = lds64(qa ^ 64); qf[2] = lds64(qa + 128); qf[3] = lds64((qa ^ 64) + 128);
                float c[8][4];
#pragma unroll
                for (int i = 0; i < 32; i++) (&c[0][0])[i] = 0.f;
#pragma unroll
                for (int s = 0; s < 4; s++)
#pragma unroll
                    for (int jj = 0; jj < 8; jj++) {
                        const uint4 u = lds128(((s & 1) ? kB : kA) + jj * 2048 + (s >> 1) * 128);
                        mma16816(c[jj], u.x, u.y, u.z, u.w, qf[s].x, qf[s].y);
                    }
                float sc[8];
#pragma unroll
                for (int jj = 0; jj < 8; jj++) sc[jj] = c[jj][0] + c[jj][3];
#pragma unroll
                for (int jj = 0; jj < 8; jj += 2) scale_scores(sc[jj], sc[jj + 1]);
                float m = fmaxf(fmaxf(fmaxf(sc[0], sc[1]), fmaxf(sc[2], sc[3])), fmaxf(fmaxf(sc[4], sc[5]), fmaxf(sc[6], sc[7])));
                m = fmaxf(m, __shfl_xor_sync(~0u, m, 5));
                m = fmaxf(m, __shfl_xor_sync(~0u, m, 8));
                m = fmaxf(m, __shfl_xor_sync(~0u, m, 16));
                const float ms = __uint_as_float(tagw(m * LOG2E, tag));
                uint32_t W0[4], W1[4];
                float l = 0.f;
#pragma unroll
                for (int i = 0; i < 4; i++) {
                    const uint32_t pp = pack_bf16(ex2(fmaf(sc[2 * i], LOG2E, -ms)), ex2(fmaf(sc[2 * i + 1], LOG2E, -ms)));
                    W0[i] = __shfl_sync(~0u, pp, 8 * t);
                    W1[i] = __shfl_sync(~0u, pp, 8 * t + 5);
                    l += bf_lo(pp) + bf_hi(pp);
                }
                l += __shfl_xor_sync(~0u, l, 5);
                l += __shfl_xor_sync(~0u, l, 8);
                l += __shfl_xor_sync(~0u, l, 16);
                if (lane == 0 || lane == 2)
                    st_relaxed128((char*)G.partML + tk * 32 + lane * 8, __float_as_uint(ms), tagw(l, tag), __float_as_uint(ms), tagw(l, tag));
                uint32_t pb[16][2];
#pragma unroll
                for (int i = 0; i < 16; i++) {
                    const uint32_t pw = (i & 1) ? W1[i >> 2] : W0[i >> 2];
                    pb[i][0] = prmt(pw, 0, (i & 2) ? sa1 : sa0);
                    pb[i][1] = prmt(pw, 0, (i & 2) ? sb1 : sb0);
                    asm volatile("" : "+r"(pb[i][0]), "+r"(pb[i][1]));
                }
                float* po = G.partO + (size_t)tk * 128 + d0;
                asm volatile("" : "+l"(po));
                if (lane == 0) note_draw(smem + SM_BAR + W_PROG, nxt, &G.clk.v, tag);
                nxt += NSTATIC;
                if (nxt >= NT - XPK && nxt < NT && lane == 0) {
                    mbar_expect_tx(bar, 16384);
                    bulk_load(slot, (const char*)P.K + (size_t)nxt * 16384, 16384, bar, pol);
                }
                mbar_wait(barV, ph);
                LAND(lane == 0, 8192 + tk);
                ph ^= 1;
                if (nxt < NT - XPK && lane == 0) {
                    mbar_expect_tx(bar, 16384);
                    bulk_load(slot, (const char*)P.K + (size_t)nxt * 16384, 16384, bar, pol);
                }
                __syncwarp();
                float acc[2][4][4];
#pragma unroll
                for (int i = 0; i < 32; i++) (&acc[0][0][0])[i] = 0.f;
#pragma unroll
                for (int jj = 0; jj < 8; jj++)
#pragma unroll
                    for (int e = 0; e < 2; e++)
#pragma unroll
                        for (int hh = 0; hh < 2; hh++) {
                            const uint4 u = lds128((e ? v1 : v0) + jj * 1024 + hh * 8192);
                            mma16816(acc[hh][(jj & 1) * 2 + e], u.x, u.y, u.z, u.w, pb[2 * jj + e][0], pb[2 * jj + e][1]);
                        }
                float r4[4];
#pragma unroll
                for (int i = 0; i < 4; i++) {
                    const float x0 = (acc[0][0][i] + acc[0][1][i]) + (acc[0][2][i] + acc[0][3][i]);
                    const float x1 = (acc[1][0][i] + acc[1][1][i]) + (acc[1][2][i] + acc[1][3][i]);
                    r4[i] = (t & 2) ? x1 : x0;
                }
                st_relaxed128(po, tagw(r4[0], tag), tagw(r4[1], tag), tagw(r4[2], tag), tagw(r4[3], tag));
                nxt = __shfl_sync(~0u, nxt, 0);
                if (nxt >= NT) break;
                tk = nxt;
            }
            STAMP(lane == 0, 16 + wi);
        }
    } else {
        float* red = (float*)(smem + SM_RED2);
        if (tid == 32) {
            const uint32_t ep0 = ld_relaxed32(&G.epoch.v);
            for (int e = 0; e < 8; e++) mbar_init(sb + SM_BAR + BAR_Q + e * 8, 1);
            for (int e = 1; e < 10; e++) mbar_init(sb + SM_BAR + BAR_W + e * 8, 1);
            mbar_init(sb + SM_BAR + BAR_BDONE, 1);
            mbar_init(sb + SM_BAR + BAR_PDONE, 1);
            mbar_init(sb + SM_BAR + BAR_QABS, 1);
            mbar_init(sb + SM_BAR + BAR_WFREE, 1);
            asm volatile("fence.mbarrier_init.release.cluster;" ::: "memory");
            asm volatile("st.volatile.shared.v4.u32 [%0], {%1, %2, %1, %1};" ::"r"(sb + SM_BAR + W_PROG), "r"(0), "r"(now_ns()) : "memory");
            *(volatile uint32_t*)(smem + SM_BAR + W_EPOCH) = ep0;
        } else if (tid == 64) {
            asm volatile("prefetch.tensormap [%0];" ::"l"(&M.m_v) : "memory");
            asm volatile("prefetch.tensormap [%0];" ::"l"(&M.m_wqB) : "memory");
            asm volatile("prefetch.tensormap [%0];" ::"l"(&M.m_wuk) : "memory");
        }
        __syncthreads();
        const uint32_t epoch = *(volatile uint32_t*)(smem + SM_BAR + W_EPOCH);
        const uint32_t tag = (epoch + 1) & 1;
        STAMP(tid == 0, 14);

        if (hasSlice) {
            const uint32_t nt = tag ^ 1;
            const int qoff = ((tid >> 5) & 1) * 4096 + 32 * j + (tid & 31);
            if (tid < 64) {
                st_relaxed32(G.qA + qoff, nt); st_relaxed32(G.qB + qoff, nt);
                if (tid < 32) {
                    st_relaxed32(G.o + 32 * j + tid, nt); st_relaxed32(G.o + 4096 + 32 * j + tid, nt);
                    st_relaxed32(G.ctx + 32 * j + tid, nt); st_relaxed32(G.ctx + 4096 + 32 * j + tid, nt);
                }
            }
            if (j == 0 && tid >= 96) st_relaxed32(&G.clk.v + lane, nt);
            if (tid >= 64 && tid < 72) st_relaxed32((uint32_t*)P.out + 8 * j + (tid - 64), 0);
            mbar_wait(sb + SM_BAR + BAR_W, 0);
            LAND(tid == 0, 17408 + 0 * 128 + j);
            STAMP(tid == 0, 15);
            uint2 bf[16];
            tall_prep(bf, sb + SM_P, warp, g, t);
            gemv_tall(sb + SM_WQ, bf, (float*)(smem + SM_RED1), warp, g, t);
            tall_finish((float*)(smem + SM_RED1), G.qA + qoff, tid, tag, 0, h >= HCLR ? 32 : 64);
            STAMP(tid == 0, 1);
            if (tid == 96) {
                mbar_expect_tx(sb + SM_BAR + BAR_W + 8, 32768);
                issue_tall(sb + SM_WQB, &M.m_wqB, j * 32, 0, sb + SM_BAR + BAR_W + 8, pol);
            }
            __syncwarp();
            tall_prep(bf, sb + SM_P + 2048, warp, g, t);
            mbar_wait(sb + SM_BAR + BAR_W + 8, 0);
            LAND(tid == 0, 17408 + 1 * 128 + j);
            gemv_tall(sb + SM_WQB, bf, red, warp, g, t);
            tall_finish(red, G.qB + qoff, tid, tag);
            if (tid == 96) {
                mbar_expect_tx(sb + SM_BAR + BAR_W + 16, 32768);
                tma_2d(sb + SM_WUK, &M.m_wuk, h * 128, qd * 128, sb + SM_BAR + BAR_W + 16, pol);
                mbar_arrive(sb + SM_BAR + BAR_WFREE);
            }
            STAMP(tid == 0, 25);
            named_bar(1, 128);
            uint4 qf[4];
            {
                const float* qp = G.qB + ((g & 1) * 32 + h) * 128 + t * 8;
                uint4 v[8];
                unsigned it = 0;
                while (true) {
                    uint32_t bad = 0;
#pragma unroll
                    for (int i = 0; i < 8; i++) v[i] = ld_relaxed128(qp + (i >> 1) * 32 + (i & 1) * 4);
#pragma unroll
                    for (int i = 0; i < 8; i++) bad |= bad4(v[i], tag);
                    if (!__any_sync(~0u, bad & 1u)) break;
                    __nanosleep(100);
                    if (++it > SPIN_LIMIT) __trap();
                }
#pragma unroll
                for (int s = 0; s < 4; s++)
                    qf[s] = make_uint4(pack_bf16(__uint_as_float(v[2 * s].x), __uint_as_float(v[2 * s].y)),
                                       pack_bf16(__uint_as_float(v[2 * s].z), __uint_as_float(v[2 * s].w)),
                                       pack_bf16(__uint_as_float(v[2 * s + 1].x), __uint_as_float(v[2 * s + 1].y)),
                                       pack_bf16(__uint_as_float(v[2 * s + 1].z), __uint_as_float(v[2 * s + 1].w)));
            }
            mbar_wait(sb + SM_BAR + BAR_W + 16, 0);
            LAND(tid == 0, 17408 + 2 * 128 + j);
#pragma unroll
            for (int jj = 0; jj < 2; jj++) {
                float c[4] = {0.f, 0.f, 0.f, 0.f};
#pragma unroll
                for (int s = 0; s < 4; s++) {
                    const uint32_t a = sb + SM_WUK + (32 * warp + 16 * jj + g) * 256 + (t + 4 * s) * 16;
                    const uint4 u = lds128(a), v = lds128(a + 2048);
                    mma16816(c, u.x, v.x, u.y, v.y, qf[s].x, qf[s].y);
                    mma16816(c, u.z, v.z, u.w, v.w, qf[s].z, qf[s].w);
                }
                const float val = (t & 2) ? ((t & 1) ? c[3] : c[2]) : ((t & 1) ? c[1] : c[0]);
                const int cc = 128 * qd + 32 * warp + 16 * jj + g + ((t & 2) ? 8 : 0);
                const int off = (cc >> 6) * 2048 + h * 64 + ((((cc & 63) >> 3) ^ (h & 7)) << 3) + (cc & 7);
                G.qabs[(t & 1) * 16384 + off] = __float2bfloat16(val);
            }
            named_bar(1, 128);
            if (tid == 0) red_release(&G.cntQabs.v);
            STAMP(tid == 0, 4);
            if (h >= HCLR) {
#pragma unroll
                for (int k = 0; k < 8; k++)
                    st_relaxed128(G.partO + (size_t)((32 + h) * 128 + 16 * k + (tid >> 3)) * 128 + qd * 32 + (tid & 7) * 4, nt, nt, nt, nt);
                if (tid < 64) st_relaxed128((char*)G.partML + ((32 + h) * 128 + qd * 32) * 32 + tid * 16, nt, nt, nt, nt);
                __threadfence();
                tall_finish((float*)(smem + SM_RED1), G.qA + qoff, tid, tag, 32, 64);
            }
        }

        if (isB) {
            const int ib = cta - NA_CTA;
            float acc[8][16];
#pragma unroll
            for (int i = 0; i < 8; i++)
#pragma unroll
                for (int k = 0; k < 16; k++) acc[i][k] = 0.f;
            float mrun[8], lrun[8];
#pragma unroll
            for (int i = 0; i < 8; i++) { mrun[i] = -INFINITY; lrun[i] = 0.f; }
            const uint64_t dQ = make_desc(sb + SM_SLOT + 5 * 32768);
            const uint64_t dP = make_desc(sb + SM_P);
            const uint32_t pst = sb + SM_P + (((lane >> 4) * 8 + (lane & 7)) * 128) + (((2 * warp + ((lane >> 3) & 1)) ^ (lane & 7)) << 4);
            mbar_wait(sb + SM_BAR + BAR_QABS, 0);
            STAMP(tid == 0, 5);
            int s0 = 0; uint32_t ph0 = 0;
            for (int it = 0; it < 16; it++) {
                int s1 = s0 + 1; uint32_t ph1 = ph0;
                if (s1 == 5) { s1 = 0; ph1 ^= 1; }
                const uint64_t dA0 = make_desc(sb + SM_SLOT + s0 * 32768), dA1 = make_desc(sb + SM_SLOT + s1 * 32768);
                float S[16];
                mbar_wait(sb + SM_BAR + BAR_BFULL + s0 * 8, ph0);
                mbar_wait(sb + SM_BAR + BAR_BFULL + s1 * 8, ph1);
                wg_fence();
#pragma unroll
                for (int k = 0; k < 32; k++) {
                    const uint64_t da = ((k < 16) ? dA0 : dA1) + (uint64_t)((((k >> 2) & 3) * 8192 + (k & 3) * 32) >> 4);
                    const uint64_t db = dQ + (uint64_t)(((k >> 2) * 4096 + (k & 3) * 32) >> 4);
                    wgmma_n32<0>(S, da, db, k > 0);
                }
                wg_commit();
                wg_wait<0>();
#pragma unroll
                for (int i = 0; i < 16; i++) S[i] *= SCALE;
                float mx[8];
#pragma unroll
                for (int i = 0; i < 8; i++) {
                    mx[i] = fmaxf(S[4 * (i >> 1) + (i & 1)], S[4 * (i >> 1) + 2 + (i & 1)]);
                    mx[i] = fmaxf(mx[i], __shfl_xor_sync(~0u, mx[i], 4));
                    mx[i] = fmaxf(mx[i], __shfl_xor_sync(~0u, mx[i], 8));
                    mx[i] = fmaxf(mx[i], __shfl_xor_sync(~0u, mx[i], 16));
                }
                if (g == 0) {
#pragma unroll
                    for (int jb = 0; jb < 4; jb++)
                        *(float2*)(red + warp * 32 + 8 * jb + 2 * t) = make_float2(mx[2 * jb], mx[2 * jb + 1]);
                }
                named_bar(1, 128);
                float al[8];
                bool chg = false;
                uint32_t R[8];
#pragma unroll
                for (int jb = 0; jb < 4; jb++) {
                    float2 a = *(float2*)(red + 8 * jb + 2 * t), b = *(float2*)(red + 32 + 8 * jb + 2 * t);
                    float2 c = *(float2*)(red + 64 + 8 * jb + 2 * t), d = *(float2*)(red + 96 + 8 * jb + 2 * t);
                    const float n0 = fmaxf(mrun[2 * jb], fmaxf(fmaxf(a.x, b.x), fmaxf(c.x, d.x)) * LOG2E);
                    const float n1 = fmaxf(mrun[2 * jb + 1], fmaxf(fmaxf(a.y, b.y), fmaxf(c.y, d.y)) * LOG2E);
                    chg |= (n0 != mrun[2 * jb]) | (n1 != mrun[2 * jb + 1]);
                    al[2 * jb] = ex2(mrun[2 * jb] - n0);
                    al[2 * jb + 1] = ex2(mrun[2 * jb + 1] - n1);
                    mrun[2 * jb] = n0; mrun[2 * jb + 1] = n1;
                    R[2 * jb]     = pack_bf16(ex2(fmaf(S[4 * jb], LOG2E, -n0)), ex2(fmaf(S[4 * jb + 1], LOG2E, -n1)));
                    R[2 * jb + 1] = pack_bf16(ex2(fmaf(S[4 * jb + 2], LOG2E, -n0)), ex2(fmaf(S[4 * jb + 3], LOG2E, -n1)));
                    lrun[2 * jb]     = fmaf(lrun[2 * jb], al[2 * jb], bf_lo(R[2 * jb]) + bf_lo(R[2 * jb + 1]));
                    lrun[2 * jb + 1] = fmaf(lrun[2 * jb + 1], al[2 * jb + 1], bf_hi(R[2 * jb]) + bf_hi(R[2 * jb + 1]));
                }
                asm volatile("stmatrix.sync.aligned.m8n8.x4.trans.shared.b16 [%0], {%1,%2,%3,%4};"
                             ::"r"(pst), "r"(R[0]), "r"(R[1]), "r"(R[2]), "r"(R[3]) : "memory");
                asm volatile("stmatrix.sync.aligned.m8n8.x4.trans.shared.b16 [%0], {%1,%2,%3,%4};"
                             ::"r"(pst + 2048), "r"(R[4]), "r"(R[5]), "r"(R[6]), "r"(R[7]) : "memory");
                asm volatile("fence.proxy.async.shared::cta;" ::: "memory");
                if (__any_sync(~0u, chg)) {
#pragma unroll
                    for (int mt = 0; mt < 8; mt++)
#pragma unroll
                        for (int k = 0; k < 16; k++) acc[mt][k] *= al[2 * (k >> 2) + (k & 1)];
                }
                named_bar(1, 128);
                wg_fence();
#pragma unroll
                for (int mt = 0; mt < 4; mt++)
#pragma unroll
                    for (int kk = 0; kk < 4; kk++)
                        wgmma_n32<1>(acc[mt], dA0 + (uint64_t)((mt * 8192 + kk * 2048) >> 4), dP + (uint64_t)((kk * 32) >> 4), 1);
                wg_commit();
#pragma unroll
                for (int mt = 0; mt < 4; mt++)
#pragma unroll
                    for (int kk = 0; kk < 4; kk++)
                        wgmma_n32<1>(acc[4 + mt], dA1 + (uint64_t)((mt * 8192 + kk * 2048) >> 4), dP + (uint64_t)((kk * 32) >> 4), 1);
                wg_commit();
                wg_wait<1>();
                if (lane == 0) mbar_arrive(sb + SM_BAR + BAR_BEMPTY + s0 * 8);
                wg_wait<0>();
                if (lane == 0) mbar_arrive(sb + SM_BAR + BAR_BEMPTY + s1 * 8);
                s0 = s1 + 1; ph0 = ph1;
                if (s0 == 5) { s0 = 0; ph0 ^= 1; }
            }
#pragma unroll
            for (int i = 0; i < 8; i++) {
                lrun[i] += __shfl_xor_sync(~0u, lrun[i], 4);
                lrun[i] += __shfl_xor_sync(~0u, lrun[i], 8);
                lrun[i] += __shfl_xor_sync(~0u, lrun[i], 16);
            }
            if (g == 0) {
#pragma unroll
                for (int jb = 0; jb < 4; jb++) {
                    *(float2*)(red + 128 + warp * 32 + 8 * jb + 2 * t) = make_float2(lrun[2 * jb], lrun[2 * jb + 1]);
                    if (warp == 0) *(float2*)(red + 256 + 8 * jb + 2 * t) = make_float2(mrun[2 * jb], mrun[2 * jb + 1]);
                }
            }
            named_bar(1, 128);
            if (tid == 0) mbar_arrive(sb + SM_BAR + BAR_BDONE);
            if (tid < 32)
                G.bml[ib * 32 + tid] = make_float2(red[256 + tid], red[128 + tid] + red[160 + tid] + red[192 + tid] + red[224 + tid]);
            float* bp = G.bpart + (size_t)ib * 16384 + (2 * t) * 512 + 16 * warp + g;
#pragma unroll
            for (int mt = 0; mt < 8; mt++)
#pragma unroll
                for (int k = 0; k < 16; k++)
                    bp[(8 * (k >> 2) + (k & 1)) * 512 + 64 * mt + ((k >> 1) & 1) * 8] = acc[mt][k];
            named_bar(1, 128);
            if (tid == 0) red_release(&G.cntB.v);
            STAMP(tid == 0, 6);
        }

        if (hasSlice) {
            if (tid == 0) {
                wait_prog(smem + SM_BAR + W_PROG, TUV);
                wait_counter(&G.cntB.v, (epoch + 1) * NB_CTA, 500);
                if (cta == 0) st_relaxed32(&G.epoch.v, epoch + 1);
                asm volatile("prefetch.tensormap [%0];" ::"l"(&M.m_uv[late]) : "memory");
                asm volatile("prefetch.tensormap [%0];" ::"l"(&M.m_w[mat]) : "memory");
            }
            named_bar(1, 128);
            if (tid == 32) mbar_arrive(sb + SM_BAR + BAR_PDONE);
            STAMP(tid == 0, 7);
            {
                const int b = tid >> 6, cp = tid & 63;
                uint2 ml[8];
#pragma unroll
                for (int i = 0; i < 8; i++) ml[i] = ld_relaxed64(G.bml + (b * 8 + i) * 32 + h);
                uint4 pv[2][8];
#pragma unroll
                for (int i = 0; i < 16; i++)
                    pv[i >> 3][i & 7] = ld_relaxed128(G.bpart + (size_t)(b * 8 + (i & 7)) * 16384 + h * 512 + (i >> 3) * 256 + 4 * cp);
                float M = __uint_as_float(ml[0].x);
#pragma unroll
                for (int i = 1; i < 8; i++) M = fmaxf(M, __uint_as_float(ml[i].x));
                float L = 0.f, wgt[8];
#pragma unroll
                for (int i = 0; i < 8; i++) {
                    wgt[i] = ex2(__uint_as_float(ml[i].x) - M);
                    L = fmaf(wgt[i], __uint_as_float(ml[i].y), L);
                }
                const float inv = 1.f / L;
#pragma unroll
                for (int x = 0; x < 2; x++) {
                    float v0 = 0.f, v1 = 0.f, v2 = 0.f, v3 = 0.f;
#pragma unroll
                    for (int i = 0; i < 8; i++) {
                        v0 = fmaf(wgt[i], __uint_as_float(pv[x][i].x), v0);
                        v1 = fmaf(wgt[i], __uint_as_float(pv[x][i].y), v1);
                        v2 = fmaf(wgt[i], __uint_as_float(pv[x][i].z), v2);
                        v3 = fmaf(wgt[i], __uint_as_float(pv[x][i].w), v3);
                    }
                    *(uint2*)(smem + SM_P + b * 1024 + x * 512 + cp * 8) = make_uint2(pack_bf16(v0 * inv, v1 * inv), pack_bf16(v2 * inv, v3 * inv));
                }
            }
            STAMP(tid == 0, 8);
        }
        {
            named_bar(1, 128);
#pragma unroll 1
            for (uint64_t plan = j < 64 ? 0xF7351260ull : (j < 124 ? (late ? 0xF75314260ull : 0xF7514603ull) : (hasSlice ? 0xF753426ull : 0xF10ull));
                 plan != 0xF; plan >>= 4) {
                const int step = plan & 15;
                if ((step & 14) == 4) {
                    const int hh = rg + 8 * warp;
                    const uint32_t real = step & 1, both = real & (mat | (warp != 3));
                    if (both) wait_ticket(smem + SM_BAR + W_PROG, mat ? NT + YB : min((33 + hh) * 128 + LAGT, NT + YLATE) + YX);
                    __syncwarp();
                    const float* src = (mat ? G.ctx : G.o) + hh * 128 + lane * 4;
                    uint4 v[2];
                    v[0] = v[1] = make_uint4(tag, tag, tag, tag);
                    uint32_t bad0 = real, bad1 = both;
                    unsigned it = 0;
                    while (true) {
                        ld_relaxed128_if(v[0], src, bad0);
                        ld_relaxed128_if(v[1], src + 4096, bad1);
                        bad0 = bad4(v[0], tag) & 1u; bad1 = bad4(v[1], tag) & 1u;
                        if (!__any_sync(~0u, bad0 | bad1)) break;
                        if (++it > SPIN_LIMIT) __trap();
                    }
#pragma unroll
                    for (int b = 0; b < 2; b++)
                        *(uint2*)(smem + SM_VEC + V_X + b * XSTR + (128 * warp + 4 * lane) * 2) =
                            make_uint2(pack_bf16(__uint_as_float(v[b].x), __uint_as_float(v[b].y)), pack_bf16(__uint_as_float(v[b].z), __uint_as_float(v[b].w)));
                    named_bar(1, 128);
                    STAMP(tid == 0, 29);
                } else if (step >= 6) {
                    const uint32_t real = step & 1;
                    const uint32_t xa = sb + SM_VEC + V_X + ((lane >> 1) & 1) * XSTR + 8 * (lane >> 3) * 2;
                    const uint32_t wa = sb + SM_SQ + 2 * 16384 + (8 * (lane >> 4) + (lane & 7)) * 128 +
                                        (((2 * warp + ((lane >> 3) & 1)) ^ (lane & 7)) << 4);
                    const uint32_t bs = sb + SM_BAR + BAR_S + 16;
                    const float* src = G.o + 4096 + (24 + rg) * 128 + lane * 4;
                    const uint32_t needx = real & (mat ^ 1);
                    uint32_t* dst = (uint32_t*)P.out + (t & 1) * 512 + mat * 256 + cg * 32 + warp * 8 + (t >> 1) * 4 + (g >> 1);
                    asm volatile("" : "+l"(dst));
                    uint4 v = make_uint4(tag, tag, tag, tag);
                    float d[4][4];
#pragma unroll
                    for (int i = 0; i < 16; i++) (&d[0][0])[i] = 0.f;
#pragma unroll 1
                    for (int u = 0; u < 3; u++) {
                        uint4 xf[4];
                        if (needx && u == 2) wait_ticket(smem + SM_BAR + W_PROG, NT + YP);
                        __syncwarp();
                        ld_relaxed128_if(v, src, needx & (u == 2));
#pragma unroll
                        for (int i = 0; i < 4; i++) xf[i] = ldsm4(xa + u * 256 + i * 64);
                        if (real) mbar_wait_nt(bs + u * 8, 0);
#pragma unroll
                        for (int i = 0; i < 4; i++) {
                            const uint4 w0 = ldsm4t(wa + u * 16384 + i * 4096), w1 = ldsm4t(wa + u * 16384 + i * 4096 + 2048);
                            mma16816(d[(i & 1) * 2], w0.x, w0.y, w0.z, w0.w, xf[i].x, xf[i].y);
                            mma16816(d[(i & 1) * 2 + 1], w1.x, w1.y, w1.z, w1.w, xf[i].z, xf[i].w);
                        }
                    }
                    unsigned it = 0;
                    while (__any_sync(~0u, bad4(v, tag) & 1u)) {
                        if (++it > SPIN_LIMIT) __trap();
                        v = ld_relaxed128(src);
                    }
                    STAMP(tid == 96, 20);
                    if (!mat)
                        *(uint2*)(smem + SM_VEC + V_X + XSTR + (384 + 4 * lane) * 2) =
                            make_uint2(pack_bf16(__uint_as_float(v.x), __uint_as_float(v.y)), pack_bf16(__uint_as_float(v.z), __uint_as_float(v.w)));
                    __syncwarp();
                    uint4 xf[4], w[4];
#pragma unroll
                    for (int i = 0; i < 4; i++) xf[i] = ldsm4(xa + 3 * 256 + i * 64);
#pragma unroll
                    for (int q = 0; q < 2; q++) {
                        if (q) {
#pragma unroll
                            for (int i = 0; i < 4; i++) {
                                d[0][i] = (d[0][i] + d[1][i]) + (d[2][i] + d[3][i]);
                                d[1][i] = d[2][i] = d[3][i] = 0.f;
                            }
                        }
                        if (real) mbar_wait_nt(bs + 24 + q * 8, 0);
#pragma unroll
                        for (int i = 0; i < 4; i++) w[i] = ldsm4t(wa + 3 * 16384 + q * 8192 + i * 2048);
#pragma unroll
                        for (int i = 0; i < 2; i++) {
                            mma16816(d[2 * i], w[2 * i].x, w[2 * i].y, w[2 * i].z, w[2 * i].w, xf[2 * q + i].x, xf[2 * q + i].y);
                            mma16816(d[2 * i + 1], w[2 * i + 1].x, w[2 * i + 1].y, w[2 * i + 1].z, w[2 * i + 1].w, xf[2 * q + i].z, xf[2 * q + i].w);
                        }
                    }
                    STAMP(tid == 64, 22);
                    float e[4];
#pragma unroll
                    for (int i = 0; i < 4; i++) e[i] = (t & 2) ? d[i][2] : d[i][0];
                    red_out(dst, ((e[0] + e[1]) + e[2]) + e[3], g, real);
                    STAMP(tid == 64, 13);
                    if (real) asm volatile("exit;");
                } else if (step >= 2) {
                    uint2 bf[16];
                    tall_prep(bf, sb + SM_P, warp, g, t);
                    if (step & 1) mbar_wait(sb + SM_BAR + BAR_S + (warp >> 1) * 8, 0);
                    LAND(tid == 64, 17408 + 3 * 128 + j);
                    gemv_tall(sb + SM_SQ, bf, red + 512, warp, g, t);
                    tall_finish(red + 512, G.ctx + ((tid >> 5) & 1) * 4096 + 32 * j + (tid & 31), tid, tag, 0, (step & 1) ? 64 : 0);
                    STAMP(tid == 0, 12);
                } else {
                    const int b = step;
                    const int hm = min(h, 31), bh = 32 * b + hm;
                    wait_ticket(smem + SM_BAR + W_PROG, min((bh + 1) * 128 + LAGT, NT + YLATE + max(hm - 27, 0) * YSL));
                    __syncwarp();
                    float* rb = red + b * 256;
                    combineA(G, bh, qd, tag, rb, tid, smem + SM_BAR + W_PROG);
                    {
                        if (tid < 32)
                            st_relaxed32(G.o + bh * 128 + 32 * qd + tid, tagw((rb[tid] + rb[32 + tid]) + (rb[64 + tid] + rb[96 + tid]), tag));
                        STAMP(tid == 0, 9 + 2 * b);
                    }
                }
            }
        }
    }
}

typedef CUresult (*EncodeFn)(CUtensorMap*, CUtensorMapDataType, cuuint32_t, void*, const cuuint64_t*, const cuuint64_t*,
                             const cuuint32_t*, const cuuint32_t*, CUtensorMapInterleave, CUtensorMapSwizzle,
                             CUtensorMapL2promotion, CUtensorMapFloatOOBfill);

}

extern "C" void kernel_launch(void* const* d_in, const int* in_sizes, int n_in, void* d_out, int out_size) {
    (void)in_sizes; (void)n_in; (void)out_size;
    static EncodeFn encode = nullptr;
    static void* scratch = nullptr;
    if (!encode) {
        void* fn = nullptr;
        cudaDriverEntryPointQueryResult st;
        cudaGetDriverEntryPoint("cuTensorMapEncodeTiled", &fn, cudaEnableDefault, &st);
        encode = (EncodeFn)fn;
        cudaGetSymbolAddress(&scratch, g_raw);
        cudaFuncSetAttribute(fused_decode_kernel, cudaFuncAttributeMaxDynamicSharedMemorySize, SM_TOTAL);
    }
    Ptrs P;
    Maps M;
    auto mk = [&](CUtensorMap* m, void* ptr, cuuint64_t cols, cuuint64_t rows, cuuint32_t bc, cuuint32_t br, CUtensorMapSwizzle sw,
                  CUtensorMapL2promotion promo) {
        const cuuint64_t gdim[2] = {cols, rows};
        const cuuint64_t gstr[1] = {cols * 2};
        const cuuint32_t box[2] = {bc, br};
        const cuuint32_t estr[2] = {1, 1};
        encode(m, CU_TENSOR_MAP_DATA_TYPE_BFLOAT16, 2, ptr, gdim, gstr, box, estr, CU_TENSOR_MAP_INTERLEAVE_NONE, sw,
               promo, CU_TENSOR_MAP_FLOAT_OOB_FILL_NONE);
    };
    mk(&M.m_wq, d_in[3], 4096, 512, 32, 256, CU_TENSOR_MAP_SWIZZLE_64B, CU_TENSOR_MAP_L2_PROMOTION_NONE);
    auto mk3 = [&](CUtensorMap* m, void* ptr, cuuint64_t cols, cuuint64_t rows) {
        const cuuint64_t gdim[3] = {64, rows, cols / 64};
        const cuuint64_t gstr[2] = {cols * 2, 128};
        const cuuint32_t box[3] = {64, 64, 2};
        const cuuint32_t estr[3] = {1, 1, 1};
        encode(m, CU_TENSOR_MAP_DATA_TYPE_BFLOAT16, 3, ptr, gdim, gstr, box, estr, CU_TENSOR_MAP_INTERLEAVE_NONE,
               CU_TENSOR_MAP_SWIZZLE_128B, CU_TENSOR_MAP_L2_PROMOTION_L2_256B, CU_TENSOR_MAP_FLOAT_OOB_FILL_NONE);
    };
    mk3(&M.m_v, d_in[2], 128, 524288);
    mk(&M.m_uv[0], d_in[9], 4096, 512, 32, 128, CU_TENSOR_MAP_SWIZZLE_64B, CU_TENSOR_MAP_L2_PROMOTION_NONE);
    mk(&M.m_uv[1], d_in[9], 4096, 512, 32, 128, CU_TENSOR_MAP_SWIZZLE_64B, CU_TENSOR_MAP_L2_PROMOTION_L2_256B);
    mk(&M.m_w[0], d_in[4], 512, 4096, 64, 64, CU_TENSOR_MAP_SWIZZLE_128B, CU_TENSOR_MAP_L2_PROMOTION_L2_256B);
    mk(&M.m_w[1], d_in[10], 512, 4096, 64, 64, CU_TENSOR_MAP_SWIZZLE_128B, CU_TENSOR_MAP_L2_PROMOTION_L2_256B);
    mk(&M.m_ckv, d_in[6], 512, 16384, 64, 64, CU_TENSOR_MAP_SWIZZLE_128B, CU_TENSOR_MAP_L2_PROMOTION_L2_256B);
    mk(&M.m_wqB, d_in[7], 4096, 512, 32, 256, CU_TENSOR_MAP_SWIZZLE_64B, CU_TENSOR_MAP_L2_PROMOTION_NONE);
    mk(&M.m_wuk, d_in[8], 4096, 512, 128, 128, CU_TENSOR_MAP_SWIZZLE_NONE, CU_TENSOR_MAP_L2_PROMOTION_L2_256B);
    P.xA = (const __nv_bfloat16*)d_in[0];
    P.K = (const __nv_bfloat16*)d_in[1];
    P.xB = (const __nv_bfloat16*)d_in[5];
    P.out = (__nv_bfloat16*)d_out;
    P.g = (Scratch*)scratch;
    cudaLaunchConfig_t cfg = {};
    cfg.gridDim = dim3(GRID);
    cfg.blockDim = dim3(NTHREADS);
    cfg.dynamicSmemBytes = SM_TOTAL;
    cfg.stream = cudaStreamPerThread;
    cudaLaunchAttribute attr;
    attr.id = cudaLaunchAttributeCooperative;
    attr.val.cooperative = 1;
    cfg.attrs = &attr;
    cfg.numAttrs = 1;
    cudaLaunchKernelEx(&cfg, fused_decode_kernel, P, M);
}
```

```cpp
#include <cuda_runtime.h>
#include <cuda_bf16.h>
#include <cuda.h>
#include <stdint.h>

namespace {

constexpr int NT       = 8192;
constexpr int GRID     = 132;
constexpr int NB_CTA   = 16;
constexpr int NA_CTA   = GRID - NB_CTA;
constexpr int NWORK    = 3;
#define YV 292
#define DV 54
#define YW 407
#define DW 68
#define DL 6
#define YX 150
#define YB 582
#define YP 605
#define XRV 330
#define TV 3200
#define PFB 16384
#define LAGT 1060
#define YLATE 120
#define YSL 70
#define YO 450
#define YOS 40
#define TUV (43 * 128)
#define XPK 80
#define FRZ 400
#define GLOOK 120
#define GL2 70
#define BIAS2 215
#define THR2 350
#define QDELAY 850
constexpr int NEARX = 400;
constexpr int GN = 8, GST = 16, GX = 512;
constexpr int JE0   = 112;
constexpr int HCLR  = 26;
constexpr int BINFL = 2;
constexpr int NSTATIC  = NA_CTA * NWORK;
constexpr unsigned DRAWS = (NT - NSTATIC) + GRID * NWORK;
static_assert(52 * 128 + LAGT + 300 <= NT && TUV + 10 * 128 <= NT, "wait_prog thresholds must be reachable");
static_assert(GX - FRZ < GRID * NWORK && GX / GST + GN <= 64, "every clock sample must be drawn and fit");
constexpr int NTHREADS = 256;
constexpr float SCALE = 0.08838834764831845f, LOG2E = 1.4426950408889634f;
constexpr unsigned SPIN_LIMIT = 1u << 22;

constexpr int SM_SLOT  = 0;
constexpr int SM_QA    = 196608;
constexpr int SM_P     = SM_QA + 16384;
constexpr int SM_RED1  = SM_P + 4096;
constexpr int SM_RED2  = SM_RED1 + 2048;
constexpr int SM_VEC   = SM_RED2 + 4096;
constexpr int SM_BAR   = SM_VEC + 3072;
constexpr int SM_TOTAL = SM_BAR + 352;
constexpr int V_X    = 512;
constexpr int BAR_FULL = 0;
constexpr int BAR_PDONE= 48;
constexpr int BAR_BDONE= 56;
constexpr int BAR_QABS = 72;
constexpr int BAR_BFULL= 80;
constexpr int BAR_BEMPTY=120;
constexpr int BAR_WFREE= 160;
constexpr int BAR_W    = 168;
constexpr int BAR_S    = 192;
constexpr int BAR_Q    = 264;
constexpr int W_EPOCH  = 328;
constexpr int W_PROG   = 336;
constexpr int SM_WQ = 3 * 32768, SM_WQB = 4 * 32768, SM_WUK = 5 * 32768;
constexpr int SM_SQ = 3 * 32768;
constexpr int XSTR = 1024 + 16;

struct __align__(128) Cnt { unsigned v; unsigned pad[31]; };
struct __align__(128) Scratch {
    Cnt epoch, ticket, cntQabs, cntB;
    float qA[64 * 128], qB[64 * 128];
    __nv_bfloat16 qabs[2 * 32 * 512];
    float  partO[NT * 128];
    float2 partML[NT * 4];
    float  bpart[NB_CTA * 32 * 512];
    float2 bml[NB_CTA * 32];
    float  ctx[32 * 4 * 2 * 128];
    float  o[2 * 4096];
    Cnt    clk, clk1;
};
__device__ __align__(128) unsigned char g_raw[sizeof(Scratch)];

__device__ __forceinline__ int slice_of(int cta) {
    return cta >= 128 ? cta : ((cta & 8) << 3) | ((cta >> 4) << 3) | (cta & 7);
}

#define STAMP(cond, i) do {} while (0)
#define LAND(cond, i) do {} while (0)

__device__ __forceinline__ void mbar_init(uint32_t bar, int cnt) {
    asm volatile("mbarrier.init.shared::cta.b64 [%0], %1;" ::"r"(bar), "r"(cnt) : "memory");
}
__device__ __forceinline__ void mbar_expect_tx(uint32_t bar, uint32_t bytes) {
    asm volatile("mbarrier.arrive.expect_tx.shared::cta.b64 _, [%0], %1;" ::"r"(bar), "r"(bytes) : "memory");
}
__device__ __forceinline__ void mbar_arrive(uint32_t bar) {
    asm volatile("mbarrier.arrive.shared::cta.b64 _, [%0];" ::"r"(bar) : "memory");
}
__device__ __forceinline__ void mbar_wait(uint32_t bar, uint32_t parity) {
    unsigned it = 0;
    while (true) {
        uint32_t ok;
        asm volatile("{\n.reg .pred p;\nmbarrier.try_wait.parity.shared::cta.b64 p, [%1], %2;\nselp.u32 %0, 1, 0, p;\n}\n"
                     : "=r"(ok) : "r"(bar), "r"(parity) : "memory");
        if (ok) break;
        if (++it > SPIN_LIMIT) __trap();
    }
}
__device__ __forceinline__ void mbar_wait_nt(uint32_t bar, uint32_t parity) {
#pragma unroll 1
    for (unsigned it = 0; it < SPIN_LIMIT; it++) {
        uint32_t ok;
        asm volatile("{\n.reg .pred p;\nmbarrier.try_wait.parity.shared::cta.b64 p, [%1], %2;\nselp.u32 %0, 1, 0, p;\n}\n"
                     : "=r"(ok) : "r"(bar), "r"(parity) : "memory");
        if (ok) break;
    }
}
__device__ __forceinline__ bool mbar_test(uint32_t bar, uint32_t parity) {
    uint32_t ok;
    asm volatile("{\n.reg .pred p;\nmbarrier.test_wait.parity.shared::cta.b64 p, [%1], %2;\nselp.u32 %0, 1, 0, p;\n}\n"
                 : "=r"(ok) : "r"(bar), "r"(parity) : "memory");
    return ok;
}
__device__ __forceinline__ void bulk_load(uint32_t dst, const void* src, uint32_t bytes, uint32_t bar, uint64_t pol) {
    asm volatile("cp.async.bulk.shared::cluster.global.mbarrier::complete_tx::bytes.L2::cache_hint [%0], [%1], %2, [%3], %4;"
                 ::"r"(dst), "l"(src), "r"(bytes), "r"(bar), "l"(pol) : "memory");
}
__device__ __forceinline__ void bulk_load_nohint(uint32_t dst, const void* src, uint32_t bytes, uint32_t bar) {
    asm volatile("cp.async.bulk.shared::cluster.global.mbarrier::complete_tx::bytes [%0], [%1], %2, [%3];"
                 ::"r"(dst), "l"(src), "r"(bytes), "r"(bar) : "memory");
}
__device__ __forceinline__ void tma_2d(uint32_t dst, const CUtensorMap* map, int c0, int c1, uint32_t bar, uint64_t pol) {
    asm volatile("cp.async.bulk.tensor.2d.shared::cluster.global.mbarrier::complete_tx::bytes.L2::cache_hint [%0], [%1, {%3, %4}], [%2], %5;"
                 ::"r"(dst), "l"(map), "r"(bar), "r"(c0), "r"(c1), "l"(pol) : "memory");
}
__device__ __forceinline__ void tma_3d(uint32_t dst, const CUtensorMap* map, int c1, int c2, uint32_t bar, uint64_t pol) {
    asm volatile("cp.async.bulk.tensor.3d.shared::cluster.global.mbarrier::complete_tx::bytes.L2::cache_hint [%0], [%1, {%3, %4, %5}], [%2], %6;"
                 ::"r"(dst), "l"(map), "r"(bar), "r"(0), "r"(c1), "r"(c2), "l"(pol) : "memory");
}
__device__ __forceinline__ void wait_prog(const unsigned char* smem_word, unsigned th) {
    unsigned it = 0;
    while (*(volatile const unsigned*)(smem_word + 8) + NSTATIC < th) {
        __nanosleep(60);
        if (++it > SPIN_LIMIT) __trap();
    }
}
__device__ __forceinline__ uint32_t now_ns() {
    uint32_t t;
    asm volatile("mov.u32 %0, %globaltimer_lo;" : "=r"(t) :: "memory");
    return t;
}
__device__ __forceinline__ void note_draw(unsigned char* smem_word, unsigned raw, unsigned* clk, uint32_t tag) {
    const uint32_t a = (uint32_t)__cvta_generic_to_shared(smem_word);
    asm volatile("st.volatile.u32 [%0], %1;" ::"l"(smem_word + 8), "r"(raw) : "memory");
    const uint32_t now = now_ns();
    if ((int)raw < NT - NSTATIC - FRZ) asm volatile("st.volatile.shared.v2.u32 [%0], {%1, %2};" ::"r"(a), "r"(raw), "r"(now) : "memory");
    const unsigned q = NT - NSTATIC - FRZ + GX - raw;
    if ((q & ~((GN - 1) * GST | GX)) == 0)
        asm volatile("st.relaxed.gpu.global.u32 [%0], %1;" ::"l"(clk + q / GST), "r"(((now + (q - GX) * 10) & ~1u) | tag) : "memory");
}
__device__ __forceinline__ void wait_ticket(const unsigned char* smem_word, int th) {
    wait_prog(smem_word, min(th, NT - NEARX));
    uint32_t tk, t0;
#pragma unroll 1
    for (unsigned it = 0; it < SPIN_LIMIT; it++) {
        asm volatile("ld.volatile.shared.v2.u32 {%0, %1}, [%2];" : "=r"(tk), "=r"(t0) : "r"((uint32_t)__cvta_generic_to_shared(smem_word)) : "memory");
        if ((int)(now_ns() - t0) >= (th - NSTATIC - (int)tk) * 10) break;
        __nanosleep(20);
    }
}
__device__ __forceinline__ bool mbar_wait_for(uint32_t bar, uint32_t parity, int n) {
    uint32_t c0, c;
    asm volatile("mov.u32 %0, %%clock;" : "=r"(c0) :: "memory");
    do {
        if (mbar_test(bar, parity)) return true;
        asm volatile("mov.u32 %0, %%clock;" : "=r"(c) :: "memory");
    } while ((int)(c - c0) < n);
    return false;
}
__device__ __forceinline__ bool elect_one() {
    uint32_t p;
    asm volatile("{\n.reg .pred p;\nelect.sync _|p, 0xffffffff;\nselp.u32 %0, 1, 0, p;\n}\n" : "=r"(p));
    return p;
}
__device__ __forceinline__ void fence_proxy_async() { asm volatile("fence.proxy.async;" ::: "memory"); }
__device__ __forceinline__ void named_bar(int id, int n) { asm volatile("bar.sync %0, %1;" ::"r"(id), "r"(n) : "memory"); }

__device__ __forceinline__ uint4 lds128(uint32_t a) {
    uint4 v;
    asm volatile("ld.shared.v4.u32 {%0,%1,%2,%3}, [%4];" : "=r"(v.x), "=r"(v.y), "=r"(v.z), "=r"(v.w) : "r"(a));
    return v;
}
__device__ __forceinline__ uint4 ldsm4(uint32_t a) {
    uint4 v;
    asm volatile("ldmatrix.sync.aligned.m8n8.x4.shared.b16 {%0,%1,%2,%3}, [%4];" : "=r"(v.x), "=r"(v.y), "=r"(v.z), "=r"(v.w) : "r"(a));
    return v;
}
__device__ __forceinline__ uint4 ldsm4t(uint32_t a) {
    uint4 v;
    asm volatile("ldmatrix.sync.aligned.m8n8.x4.trans.shared.b16 {%0,%1,%2,%3}, [%4];" : "=r"(v.x), "=r"(v.y), "=r"(v.z), "=r"(v.w) : "r"(a));
    return v;
}
__device__ __forceinline__ uint2 lds64(uint32_t a) {
    uint2 v;
    asm volatile("ld.shared.v2.u32 {%0,%1}, [%2];" : "=r"(v.x), "=r"(v.y) : "r"(a));
    return v;
}
__device__ __forceinline__ uint4 ld_relaxed128(const void* p) {
    uint4 v;
    asm volatile("ld.relaxed.gpu.global.v4.u32 {%0,%1,%2,%3}, [%4];" : "=r"(v.x), "=r"(v.y), "=r"(v.z), "=r"(v.w) : "l"(p) : "memory");
    return v;
}
__device__ __forceinline__ uint2 ld_relaxed64(const void* p) {
    uint2 v;
    asm volatile("ld.relaxed.gpu.global.v2.u32 {%0,%1}, [%2];" : "=r"(v.x), "=r"(v.y) : "l"(p) : "memory");
    return v;
}
__device__ __forceinline__ uint32_t ld_relaxed32(const void* p) {
    uint32_t v;
    asm volatile("ld.relaxed.gpu.global.u32 %0, [%1];" : "=r"(v) : "l"(p) : "memory");
    return v;
}
__device__ __forceinline__ uint32_t ld_acquire32(const void* p) {
    uint32_t v;
    asm volatile("ld.acquire.gpu.global.u32 %0, [%1];" : "=r"(v) : "l"(p) : "memory");
    return v;
}
__device__ __forceinline__ void st_relaxed128(void* p, uint32_t a, uint32_t b, uint32_t c, uint32_t d) {
    asm volatile("st.relaxed.gpu.global.v4.u32 [%0], {%1,%2,%3,%4};" ::"l"(p), "r"(a), "r"(b), "r"(c), "r"(d) : "memory");
}
__device__ __forceinline__ void red_release(unsigned* p) {
    asm volatile("red.release.gpu.global.add.u32 [%0], 1;" ::"l"(p) : "memory");
}
__device__ __forceinline__ void wait_counter(const unsigned* p, unsigned target, unsigned ns) {
    unsigned it = 0;
    while ((int)(ld_acquire32(p) - target) < 0) {
        __nanosleep(ns);
        if (++it > SPIN_LIMIT) __trap();
    }
}
__device__ __forceinline__ uint32_t prmt(uint32_t a, uint32_t b, uint32_t s) {
    uint32_t d;
    asm("prmt.b32 %0, %1, %2, %3;" : "=r"(d) : "r"(a), "r"(b), "r"(s));
    return d;
}
__device__ __forceinline__ uint32_t pack_bf16(float lo, float hi) {
    uint32_t d;
    asm("cvt.rn.bf16x2.f32 %0, %1, %2;" : "=r"(d) : "f"(hi), "f"(lo));
    return d;
}
__device__ __forceinline__ float ex2(float x) {
    float y;
    asm("ex2.approx.ftz.f32 %0, %1;" : "=f"(y) : "f"(x));
    return y;
}
__device__ __forceinline__ float bf_lo(uint32_t v) { return __uint_as_float(v << 16); }
__device__ __forceinline__ float bf_hi(uint32_t v) { return __uint_as_float(v & 0xffff0000u); }
__device__ __forceinline__ void scale_scores(float& a, float& b) {
    uint32_t p = pack_bf16(a, b);
    p = pack_bf16(bf_lo(p) * SCALE, bf_hi(p) * SCALE);
    a = bf_lo(p); b = bf_hi(p);
}
__device__ __forceinline__ uint32_t tagw(float v, uint32_t tag) {
    uint32_t d;
    asm("lop3.b32 %0, %1, 0xfffffffe, %2, 0xEA;" : "=r"(d) : "r"(__float_as_uint(v)), "r"(tag));
    return d;
}
__device__ __forceinline__ uint32_t bad2(uint32_t x, uint32_t y, uint32_t tag) {
    uint32_t d;
    asm("lop3.b32 %0, %1, %2, %3, 0x7E;" : "=r"(d) : "r"(x), "r"(y), "r"(tag));
    return d;
}
__device__ __forceinline__ uint32_t bad4(const uint4& v, uint32_t tag) { return bad2(v.x, v.y, tag) | bad2(v.z, v.w, tag); }
__device__ __forceinline__ void ld_relaxed128_if(uint4& v, const void* p, uint32_t c) {
    asm volatile("{\n.reg .pred p;\nsetp.ne.u32 p, %5, 0;\n@p ld.relaxed.gpu.global.v4.u32 {%0,%1,%2,%3}, [%4];\n}\n"
                 : "+r"(v.x), "+r"(v.y), "+r"(v.z), "+r"(v.w) : "l"(p), "r"(c) : "memory");
}
__device__ __forceinline__ void ld_relaxed64_if(uint2& v, const void* p, uint32_t c) {
    asm volatile("{\n.reg .pred p;\nsetp.ne.u32 p, %3, 0;\n@p ld.relaxed.gpu.global.v2.u32 {%0,%1}, [%2];\n}\n"
                 : "+r"(v.x), "+r"(v.y) : "l"(p), "r"(c) : "memory");
}
__device__ __forceinline__ void st_relaxed32(void* p, uint32_t a) {
    asm volatile("st.relaxed.gpu.global.u32 [%0], %1;" ::"l"(p), "r"(a) : "memory");
}
__device__ __forceinline__ void red_out(uint32_t* word, float v, int col, uint32_t go) {
    const uint32_t pk = (col & 1) ? pack_bf16(-0.f, v) : pack_bf16(v, -0.f);
    asm volatile("{\n.reg .pred p;\nsetp.ne.u32 p, %2, 0;\n@p red.relaxed.gpu.global.add.noftz.bf16x2 [%0], %1;\n}\n"
                 ::"l"(word), "r"(pk), "r"(go) : "memory");
}
__device__ __forceinline__ void mma16816(float (&c)[4], uint32_t a0, uint32_t a1, uint32_t a2, uint32_t a3,
                                         uint32_t b0, uint32_t b1) {
    asm("mma.sync.aligned.m16n8k16.row.col.f32.bf16.bf16.f32 {%0,%1,%2,%3}, {%4,%5,%6,%7}, {%8,%9}, {%0,%1,%2,%3};"
        : "+f"(c[0]), "+f"(c[1]), "+f"(c[2]), "+f"(c[3])
        : "r"(a0), "r"(a1), "r"(a2), "r"(a3), "r"(b0), "r"(b1));
}
__device__ __forceinline__ uint64_t make_desc(uint32_t addr) {
    return (uint64_t)((addr & 0x3FFFF) >> 4) | ((uint64_t)1 << 16) | ((uint64_t)64 << 32) | ((uint64_t)1 << 62);
}
template <int TRANS_A>
__device__ __forceinline__ void wgmma_n32(float (&d)[16], uint64_t da, uint64_t db, int scale_d) {
    asm volatile("{\n.reg .pred p;\nsetp.ne.b32 p, %18, 0;\n"
                 "wgmma.mma_async.sync.aligned.m64n32k16.f32.bf16.bf16 "
                 "{%0,%1,%2,%3,%4,%5,%6,%7,%8,%9,%10,%11,%12,%13,%14,%15}, %16, %17, p, 1, 1, %19, 0;\n}\n"
                 : "+f"(d[0]), "+f"(d[1]), "+f"(d[2]), "+f"(d[3]), "+f"(d[4]), "+f"(d[5]), "+f"(d[6]), "+f"(d[7]),
                   "+f"(d[8]), "+f"(d[9]), "+f"(d[10]), "+f"(d[11]), "+f"(d[12]), "+f"(d[13]), "+f"(d[14]), "+f"(d[15])
                 : "l"(da), "l"(db), "r"(scale_d), "n"(TRANS_A));
}
__device__ __forceinline__ void wg_fence()  { asm volatile("wgmma.fence.sync.aligned;" ::: "memory"); }
__device__ __forceinline__ void wg_commit() { asm volatile("wgmma.commit_group.sync.aligned;" ::: "memory"); }
template <int N> __device__ __forceinline__ void wg_wait() { asm volatile("wgmma.wait_group.sync.aligned %0;" ::"n"(N) : "memory"); }

__device__ __forceinline__ void issue_tall(uint32_t dst, const CUtensorMap* map, int col, int row, uint32_t bar, uint64_t pol) {
    tma_2d(dst, map, col, row, bar, pol);
    tma_2d(dst + 16384, map, col, row + 256, bar, pol);
}
__device__ __forceinline__ void tall_prep(uint2 (&bf)[16], uint32_t xbase, int w4, int g, int t) {
    const uint32_t xp = xbase + ((g >> 1) & 1) * 1024 + w4 * 256 + (t >> 1) * 8;
    const uint32_t sel = (g & 1) ? ((t & 1) ? 0x3244u : 0x1044u) : ((t & 1) ? 0x4432u : 0x4410u);
#pragma unroll
    for (int i = 0; i < 16; i++) {
        const uint2 xw = lds64(xp + i * 16);
        bf[i] = make_uint2(prmt(xw.x, 0, sel), prmt(xw.y, 0, sel));
    }
}
__device__ __forceinline__ void gemv_tall(uint32_t wbase, const uint2 (&bf)[16], float* red, int w4, int g, int t) {
    const uint32_t wu = wbase + (128 * w4 + (t & 1) + 4 * (t >> 1)) * 64 + (((g >> 1) ^ (t & 2)) << 4) + (g & 1) * 8;
    const uint32_t wv = (wu + 128) ^ 16;
    float a[4][4];
#pragma unroll
    for (int i = 0; i < 16; i++) (&a[0][0])[i] = 0.f;
#pragma unroll
    for (int i = 0; i < 16; i++) {
        const uint2 u = lds64(wu + i * 512), v = lds64(wv + i * 512);
        mma16816(a[i & 3], u.x, u.y, v.x, v.y, bf[i].x, bf[i].y);
    }
    if (t < 2)
        *(float4*)(red + (w4 * 2 + t) * 32 + 4 * g) =
            make_float4((a[0][0] + a[1][0]) + (a[2][0] + a[3][0]), (a[0][1] + a[1][1]) + (a[2][1] + a[3][1]),
                        (a[0][2] + a[1][2]) + (a[2][2] + a[3][2]), (a[0][3] + a[1][3]) + (a[2][3] + a[3][3]));
}
__device__ __forceinline__ void tall_finish(const float* red, float* dst, int tid, uint32_t tag, int lo = 0, int hi = 64) {
    named_bar(1, 128);
    if (tid >= lo && tid < hi) {
        st_relaxed32(dst, tagw((red[tid] + red[64 + tid]) + (red[128 + tid] + red[192 + tid]), tag));
    }
}

__device__ __forceinline__ void combineA(Scratch& G, int bh, int dq, uint32_t tag, float* red, int tid, const unsigned char* prog) {
    const int r = tid >> 3, c4 = tid & 7, w4 = tid >> 5, lane = tid & 31;
    const float2* ml = G.partML + (bh * 128 + r) * 4;
    const float* po = G.partO + (size_t)(bh * 128 + r) * 128 + dq * 32 + c4 * 4;
    uint2 m[8];
    uint4 o[8];
    uint32_t bad[8];
    STAMP(tid == 0 && bh >= 32, 28);
#pragma unroll
    for (int k = 0; k < 8; k++) m[k] = ld_relaxed64(ml + 64 * k);
#pragma unroll
    for (int k = 0; k < 8; k++) {
        o[k] = make_uint4(~tag, ~tag, ~tag, ~tag);
        ld_relaxed128_if(o[k], po + (size_t)k * 16 * 128, bh < 60);
    }
    unsigned it = 0;
    while (true) {
        uint32_t any = 0;
#pragma unroll
        for (int k = 0; k < 8; k++) { bad[k] = bad2(m[k].x, m[k].y, tag) & 1u; any |= bad[k]; }
        if (!__any_sync(~0u, any)) break;
#pragma unroll
        for (int k = 0; k < 8; k++) ld_relaxed64_if(m[k], ml + 64 * k, bad[k]);
        if (++it > SPIN_LIMIT) __trap();
    }
    STAMP(tid == 0 && bh >= 32, 30);
    STAMP(tid == 0 && bh >= 32, 19);
    float M = fmaxf(fmaxf(fmaxf(__uint_as_float(m[0].x), __uint_as_float(m[1].x)), fmaxf(__uint_as_float(m[2].x), __uint_as_float(m[3].x))),
                    fmaxf(fmaxf(__uint_as_float(m[4].x), __uint_as_float(m[5].x)), fmaxf(__uint_as_float(m[6].x), __uint_as_float(m[7].x))));
    M = fmaxf(M, __shfl_xor_sync(~0u, M, 8));
    M = fmaxf(M, __shfl_xor_sync(~0u, M, 16));
    float wgt[8], L = 0.f;
#pragma unroll
    for (int k = 0; k < 8; k++) {
        wgt[k] = ex2(__uint_as_float(m[k].x) - M);
        L = fmaf(wgt[k], __uint_as_float(m[k].y), L);
    }
    L += __shfl_xor_sync(~0u, L, 8);
    L += __shfl_xor_sync(~0u, L, 16);
    if (lane == 0) { red[128 + w4] = M; red[132 + w4] = L; }
    named_bar(1, 128);
    {
        const float4 Mw = *(float4*)(red + 128), Lw = *(float4*)(red + 132);
        const float Mx = fmaxf(fmaxf(Mw.x, Mw.y), fmaxf(Mw.z, Mw.w));
        const float Lt = (ex2(Mw.x - Mx) * Lw.x + ex2(Mw.y - Mx) * Lw.y) + (ex2(Mw.z - Mx) * Lw.z + ex2(Mw.w - Mx) * Lw.w);
        const float f = ex2(M - Mx) / Lt;
#pragma unroll
        for (int k = 0; k < 8; k++) wgt[k] *= f;
    }
    STAMP(tid == 0 && bh >= 32, 23);
    if (bh >= 60) wait_ticket(prog, NT + YO + (bh - 63) * YOS);
    while (true) {
        uint32_t any = 0;
#pragma unroll
        for (int k = 0; k < 8; k++) { bad[k] = bad4(o[k], tag) & 1u; any |= bad[k]; }
        if (!__any_sync(~0u, any)) break;
#pragma unroll
        for (int k = 0; k < 8; k++) ld_relaxed128_if(o[k], po + (size_t)k * 16 * 128, bad[k]);
        if (++it > SPIN_LIMIT) __trap();
    }
    STAMP(tid == 0 && bh >= 32, 31);
    float a0 = 0.f, a1 = 0.f, a2 = 0.f, a3 = 0.f, b0 = 0.f, b1 = 0.f, b2 = 0.f, b3 = 0.f;
#pragma unroll
    for (int k = 0; k < 8; k += 2) {
        a0 = fmaf(wgt[k], __uint_as_float(o[k].x), a0); b0 = fmaf(wgt[k + 1], __uint_as_float(o[k + 1].x), b0);
        a1 = fmaf(wgt[k], __uint_as_float(o[k].y), a1); b1 = fmaf(wgt[k + 1], __uint_as_float(o[k + 1].y), b1);
        a2 = fmaf(wgt[k], __uint_as_float(o[k].z), a2); b2 = fmaf(wgt[k + 1], __uint_as_float(o[k + 1].z), b2);
        a3 = fmaf(wgt[k], __uint_as_float(o[k].w), a3); b3 = fmaf(wgt[k + 1], __uint_as_float(o[k + 1].w), b3);
    }
    a0 += b0; a1 += b1; a2 += b2; a3 += b3;
#pragma unroll
    for (int s = 8; s <= 16; s <<= 1) {
        a0 += __shfl_xor_sync(~0u, a0, s);
        a1 += __shfl_xor_sync(~0u, a1, s);
        a2 += __shfl_xor_sync(~0u, a2, s);
        a3 += __shfl_xor_sync(~0u, a3, s);
    }
    if (lane < 8) *(float4*)(red + w4 * 32 + c4 * 4) = make_float4(a0, a1, a2, a3);
    named_bar(1, 128);
    STAMP(tid == 0 && bh >= 32, 24);
}

struct Ptrs {
    const __nv_bfloat16 *K, *xA, *xB;
    __nv_bfloat16* out;
    Scratch* g;
};
struct Maps { CUtensorMap m_wq, m_v, m_ckv, m_wqB, m_wuk, m_uv[2], m_w[2]; };

__global__ void __launch_bounds__(NTHREADS, 1)
fused_decode_kernel(const Ptrs P, const __grid_constant__ Maps M) {
    extern __shared__ __align__(1024) unsigned char smem[];
    const uint32_t sb = (uint32_t)__cvta_generic_to_shared(smem);
    uint64_t pol;
    asm("createpolicy.fractional.L2::evict_first.b64 %0, 1.0;" : "=l"(pol));
    asm volatile("{\n.reg .pred p;\nsetp.lt.u32 p, %3, 32;\n@p cp.async.bulk.prefetch.L2.global.L2::cache_hint [%0], %1, %2;\n}\n"
                 ::"l"((const char*)P.K + (blockIdx.x << 14)), "n"(PFB), "l"(pol), "r"(threadIdx.x) : "memory");
    if (threadIdx.x < 32 && elect_one()) {
        mbar_init(sb + SM_BAR + BAR_FULL, 1);
        mbar_init(sb + SM_BAR + BAR_FULL + 16, 1);
        mbar_init(sb + SM_BAR + BAR_W, 1);
        asm volatile("fence.mbarrier_init.release.cluster;" ::: "memory");
        if (blockIdx.x < NA_CTA) {
            mbar_expect_tx(sb + SM_BAR + BAR_FULL, 16384);
            bulk_load(sb + SM_SLOT, (const char*)P.K + (blockIdx.x << 14), 16384, sb + SM_BAR + BAR_FULL, pol);
        }
        if (blockIdx.x < 128) {
            mbar_expect_tx(sb + SM_BAR + BAR_W, 32768 + 4096);
            issue_tall(sb + SM_WQ, &M.m_wq, slice_of(blockIdx.x) * 32, 0, sb + SM_BAR + BAR_W, pol);
            bulk_load_nohint(sb + SM_P, P.xA, 2048, sb + SM_BAR + BAR_W);
            bulk_load_nohint(sb + SM_P + 2048, P.xB, 2048, sb + SM_BAR + BAR_W);
        }
        if (blockIdx.x < NA_CTA) {
            mbar_expect_tx(sb + SM_BAR + BAR_FULL + 16, 16384);
            bulk_load(sb + SM_SLOT + 32768, (const char*)P.K + ((blockIdx.x + NA_CTA) << 14), 16384, sb + SM_BAR + BAR_FULL + 16, pol);
        }
    }
    const int tid = threadIdx.x, warp = __shfl_sync(~0u, tid >> 5, 0), lane = tid & 31;
    const int g = lane >> 2, t = lane & 3;
    const int cta = blockIdx.x;
    Scratch& G = *P.g;
    const bool isB = cta >= NA_CTA;
    const bool hasSlice = cta < 128;
    const int j = slice_of(cta), h = j >> 2, qd = cta & 3;
    const int mat = j >> 6, cg = j & 7, rg = (j >> 3) & 7;
    const bool late = j < JE0 || j >= 124;
    STAMP(tid == 32, 0);
    if (warp == 7) {
        __syncthreads();
        const uint32_t epoch = *(volatile uint32_t*)(smem + SM_BAR + W_EPOCH);
        const uint32_t tag = (epoch + 1) & 1;
        if (!isB) { mbar_wait(sb + SM_BAR + BAR_W, 0); __nanosleep(QDELAY); }
#pragma unroll 1
        for (int i = 0; i < 8; i++) {
            if (i == 4 && !isB) wait_prog(smem + SM_BAR + W_PROG, 16 * 128);
            if (i == 0 && isB) { mbar_wait(sb + SM_BAR + BAR_QABS, 0); __nanosleep(8000); }
            uint4 v[8];
            uint32_t bad[8];
#pragma unroll
            for (int k = 0; k < 8; k++) { bad[k] = 1; v[k] = make_uint4(0, 0, 0, 0); }
            unsigned it = 0;
            while (true) {
#pragma unroll
                for (int k = 0; k < 8; k++) ld_relaxed128_if(v[k], G.qA + (8 * i + k) * 128 + lane * 4, bad[k]);
                uint32_t any = 0;
#pragma unroll
                for (int k = 0; k < 8; k++) { bad[k] = bad4(v[k], tag) & 1u; any |= bad[k]; }
                if (!__any_sync(~0u, any)) break;
                __nanosleep(40);
                if (++it > SPIN_LIMIT) __trap();
            }
#pragma unroll
            for (int k = 0; k < 8; k++) {
                uint32_t* dst = (uint32_t*)(smem + SM_QA + (8 * i + k) * 256 + (lane >> 1) * 16 + (lane & 1) * 4);
                dst[0] = pack_bf16(__uint_as_float(v[k].x), __uint_as_float(v[k].y));
                dst[2] = pack_bf16(__uint_as_float(v[k].z), __uint_as_float(v[k].w));
            }
            __syncwarp();
            if (lane == 0) mbar_arrive(sb + SM_BAR + BAR_Q + i * 8);
            STAMP(lane == 0 && i == 0, 2);
        }
        STAMP(lane == 0, 21);
        if (hasSlice) mbar_wait(sb + SM_BAR + BAR_PDONE, 0);
#pragma unroll 1
        for (int p = 0; p < 12; p++) {
            const bool uv = p < 4;
            if (p == (late ? 0 : 4)) {
                uint32_t tref = 0;
#pragma unroll 1
                for (int k = 0; k < 2; k++) {
                    wait_ticket(smem + SM_BAR + W_PROG, NT - FRZ + (k ? GX + GL2 : GLOOK));
                    uint32_t v;
                    unsigned it = 0;
                    while (true) {
                        v = ld_relaxed32(&G.clk.v + (k ? 0 : GX / GST) + (lane & (GN - 1)));
                        if (!__any_sync(~0u, (v ^ tag) & 1u)) break;
                        __nanosleep(200);
                        if (++it > SPIN_LIMIT) __trap();
                    }
                    const uint32_t v0 = __shfl_sync(~0u, v, 0);
                    v = v0 + (__reduce_add_sync(~0u, (int)(v - v0)) >> 5) - (k ? BIAS2 : 0);
                    if ((!k || (int)(v - tref) > THR2) && lane == 0)
                        asm volatile("st.volatile.shared.v2.u32 [%0], {%1, %2};" ::"r"(sb + SM_BAR + W_PROG), "r"(NT - NSTATIC - FRZ), "r"(v) : "memory");
                    tref = v;
                    __syncwarp();
                }
                if (!hasSlice) break;
            }
            if (lane == 0) {
                const int r = uv ? p * 128 : (p - 4) * 64;
                if (!uv || late)
                    wait_ticket(smem + SM_BAR + W_PROG, NT + (uv ? YV + (p * DV >> 1) : YW + ((p - 4) * DW >> 1) + (p == 11 ? DL : 0)));
                STAMP(p == 4, 10);
                const uint32_t bar = sb + SM_BAR + BAR_S + (p < 11 ? p >> 1 : 6) * 8;
                if (!(p & 1) || p == 11) mbar_expect_tx(bar, p < 10 ? 16384 : 8192);
                tma_2d(sb + SM_SQ + p * 8192, uv ? &M.m_uv[late] : &M.m_w[mat], uv ? j * 32 : cg * 64,
                       uv ? r : (rg + 8 * (r >> 7)) * 128 + (r & 127), bar, pol);
            }
            __syncwarp();
        }
    } else if (warp >= 4) {
        const int wi = warp - 4;
        const uint32_t slot = sb + SM_SLOT + wi * 32768;
        const uint32_t bar = sb + SM_BAR + BAR_FULL + wi * 16, barV = bar + 8;
        unsigned tk = wi * NA_CTA + cta;
        const bool ev = wi == 2;
        if (lane == 0) {
            if (ev) mbar_init(bar, 1);
            mbar_init(barV, 1);
            if (isB && wi == 0) {
                for (int s = 0; s < 5; s++) {
                    mbar_init(sb + SM_BAR + BAR_BFULL + s * 8, 1);
                    mbar_init(sb + SM_BAR + BAR_BEMPTY + s * 8, 4);
                }
            }
            asm volatile("fence.mbarrier_init.release.cluster;" ::: "memory");
        }
        __syncthreads();
        const uint32_t epoch = *(volatile uint32_t*)(smem + SM_BAR + W_EPOCH);
        const uint32_t tag = (epoch + 1) & 1;

        bool active = true;
        if (isB) {
            if (wi == 1 && lane == 0) {
                wait_counter(&G.cntQabs.v, (epoch + 1) * 128, 64);
                fence_proxy_async();
                mbar_expect_tx(sb + SM_BAR + BAR_QABS, 32768);
                bulk_load_nohint(sb + SM_SLOT + 5 * 32768, G.qabs + ((cta - NA_CTA) >> 3) * 16384, 32768, sb + SM_BAR + BAR_QABS);
            }
            if (wi == 0 && lane == 0) {
                const int ib = cta - NA_CTA;
                int s = 0, sl = 0; uint32_t ph = 1, phl = 0;
                for (int u = 0; u < 32; u++) {
                    if (u >= BINFL) {
                        mbar_wait(sb + SM_BAR + BAR_BFULL + sl * 8, phl);
                        LAND(true, 16384 + ib * 32 + u);
                        if (++sl == 5) { sl = 0; phl ^= 1; }
                    }
                    if (u == 3 && hasSlice) mbar_wait(sb + SM_BAR + BAR_WFREE, 0);
                    mbar_wait(sb + SM_BAR + BAR_BEMPTY + s * 8, ph);
                    const uint32_t fb = sb + SM_BAR + BAR_BFULL + s * 8;
                    const int row = (ib >> 3) * 8192 + ((u >> 1) * 8 + (ib & 7)) * 64;
                    mbar_expect_tx(fb, 32768);
                    for (int x = 0; x < 4; x++)
                        tma_2d(sb + SM_SLOT + s * 32768 + x * 8192, &M.m_ckv, ((u & 1) * 4 + x) * 64, row, fb, pol);
                    if (++s == 5) { s = 0; ph ^= 1; }
                }
            }
            __syncwarp();
            mbar_wait(sb + SM_BAR + BAR_BDONE, 0);
            if (lane == 0) {
                tk = atomicInc(&G.ticket.v, DRAWS - 1);
                note_draw(smem + SM_BAR + W_PROG, tk, &G.clk.v, tag);
                tk += NSTATIC;
            }
            tk = __shfl_sync(~0u, tk, 0);
            active = tk < NT;
        } else if (ev) {
            __syncwarp();
            mbar_wait(sb + SM_BAR + BAR_W + 8, 0);
        }
        if (active) {
            if ((isB || ev) && lane == 0) {
                mbar_expect_tx(bar, 16384);
                bulk_load(slot, (const char*)P.K + (size_t)tk * 16384, 16384, bar, pol);
            }
            const uint32_t kA = slot + g * 256 + t * 16 + (g & 1) * 64, kB = kA ^ 64;
            const uint32_t qo = t * 16 + ((g >> 1) & 1) * 64 + (g & 1) * 8;
            const uint32_t v0 = slot + 16384 + (2 * t) * 128 + ((g ^ (2 * t)) << 4), v1 = (v0 + 128) ^ 16;
            const uint32_t sl0 = (g & 1) ? 0x1044u : 0x4410u, sl1 = (g & 1) ? 0x3244u : 0x4432u;
            const uint32_t sa0 = (g & 2) ? 0x4444u : sl0, sa1 = (g & 2) ? 0x4444u : sl1;
            const uint32_t sb0 = (g & 2) ? sl0 : 0x4444u, sb1 = (g & 2) ? sl1 : 0x4444u;
            const int d0 = 64 * (t >> 1) + 8 * g + 4 * (t & 1);
            uint32_t ph = 0;
            while (true) {
                const uint32_t qa = sb + SM_QA + (tk >> 7) * 256 + qo;
                bool vout = false;
                if (XRV && lane == 0 && tk >= NT - XRV && !mbar_wait_for(bar, ph, TV)) {
                    mbar_expect_tx(barV, 16384);
                    tma_3d(slot + 16384, &M.m_v, tk * 64, 0, barV, pol);
                    vout = true;
                }
                if (XRV) __syncwarp();
                mbar_wait(bar, ph);
                LAND(lane == 0, tk);
                unsigned nxt = 0;
                if (lane == 0) {
                    if (!vout) {
                        mbar_expect_tx(barV, 16384);
                        tma_3d(slot + 16384, &M.m_v, tk * 64, 0, barV, pol);
                    }
                    asm volatile("atom.relaxed.gpu.global.inc.u32 %0, [%1], %2;" : "=r"(nxt) : "l"(&G.ticket.v), "r"(DRAWS - 1) : "memory");
                }
                __syncwarp();
                mbar_wait(sb + SM_BAR + BAR_Q + (tk >> 10) * 8, 0);
                STAMP(tid == 128 && tk < NSTATIC, 3);
                uint2 qf[4];
                qf[0] = lds64(qa); qf[1] = lds64(qa ^ 64); qf[2] = lds64(qa + 128); qf[3] = lds64((qa ^ 64) + 128);
                float c[8][4];
#pragma unroll
                for (int i = 0; i < 32; i++) (&c[0][0])[i] = 0.f;
#pragma unroll
                for (int s = 0; s < 4; s++)
#pragma unroll
                    for (int jj = 0; jj < 8; jj++) {
                        const uint4 u = lds128(((s & 1) ? kB : kA) + jj * 2048 + (s >> 1) * 128);
                        mma16816(c[jj], u.x, u.y, u.z, u.w, qf[s].x, qf[s].y);
                    }
                float sc[8];
#pragma unroll
                for (int jj = 0; jj < 8; jj++) sc[jj] = c[jj][0] + c[jj][3];
#pragma unroll
                for (int jj = 0; jj < 8; jj += 2) scale_scores(sc[jj], sc[jj + 1]);
                float m = fmaxf(fmaxf(fmaxf(sc[0], sc[1]), fmaxf(sc[2], sc[3])), fmaxf(fmaxf(sc[4], sc[5]), fmaxf(sc[6], sc[7])));
                m = fmaxf(m, __shfl_xor_sync(~0u, m, 5));
                m = fmaxf(m, __shfl_xor_sync(~0u, m, 8));
                m = fmaxf(m, __shfl_xor_sync(~0u, m, 16));
                const float ms = __uint_as_float(tagw(m * LOG2E, tag));
                uint32_t W0[4], W1[4];
                float l = 0.f;
#pragma unroll
                for (int i = 0; i < 4; i++) {
                    const uint32_t pp = pack_bf16(ex2(fmaf(sc[2 * i], LOG2E, -ms)), ex2(fmaf(sc[2 * i + 1], LOG2E, -ms)));
                    W0[i] = __shfl_sync(~0u, pp, 8 * t);
                    W1[i] = __shfl_sync(~0u, pp, 8 * t + 5);
                    l += bf_lo(pp) + bf_hi(pp);
                }
                l += __shfl_xor_sync(~0u, l, 5);
                l += __shfl_xor_sync(~0u, l, 8);
                l += __shfl_xor_sync(~0u, l, 16);
                if (lane == 0 || lane == 2)
                    st_relaxed128((char*)G.partML + tk * 32 + lane * 8, __float_as_uint(ms), tagw(l, tag), __float_as_uint(ms), tagw(l, tag));
                uint32_t pb[16][2];
#pragma unroll
                for (int i = 0; i < 16; i++) {
                    const uint32_t pw = (i & 1) ? W1[i >> 2] : W0[i >> 2];
                    pb[i][0] = prmt(pw, 0, (i & 2) ? sa1 : sa0);
                    pb[i][1] = prmt(pw, 0, (i & 2) ? sb1 : sb0);
                    asm volatile("" : "+r"(pb[i][0]), "+r"(pb[i][1]));
                }
                float* po = G.partO + (size_t)tk * 128 + d0;
                asm volatile("" : "+l"(po));
                if (lane == 0) note_draw(smem + SM_BAR + W_PROG, nxt, &G.clk.v, tag);
                nxt += NSTATIC;
                if (nxt >= NT - XPK && nxt < NT && lane == 0) {
                    mbar_expect_tx(bar, 16384);
                    bulk_load(slot, (const char*)P.K + (size_t)nxt * 16384, 16384, bar, pol);
                }
                mbar_wait(barV, ph);
                LAND(lane == 0, 8192 + tk);
                ph ^= 1;
                if (nxt < NT - XPK && lane == 0) {
                    mbar_expect_tx(bar, 16384);
                    bulk_load(slot, (const char*)P.K + (size_t)nxt * 16384, 16384, bar, pol);
                }
                __syncwarp();
                float acc[2][4][4];
#pragma unroll
                for (int i = 0; i < 32; i++) (&acc[0][0][0])[i] = 0.f;
#pragma unroll
                for (int jj = 0; jj < 8; jj++)
#pragma unroll
                    for (int e = 0; e < 2; e++)
#pragma unroll
                        for (int hh = 0; hh < 2; hh++) {
                            const uint4 u = lds128((e ? v1 : v0) + jj * 1024 + hh * 8192);
                            mma16816(acc[hh][(jj & 1) * 2 + e], u.x, u.y, u.z, u.w, pb[2 * jj + e][0], pb[2 * jj + e][1]);
                        }
                float r4[4];
#pragma unroll
                for (int i = 0; i < 4; i++) {
                    const float x0 = (acc[0][0][i] + acc[0][1][i]) + (acc[0][2][i] + acc[0][3][i]);
                    const float x1 = (acc[1][0][i] + acc[1][1][i]) + (acc[1][2][i] + acc[1][3][i]);
                    r4[i] = (t & 2) ? x1 : x0;
                }
                st_relaxed128(po, tagw(r4[0], tag), tagw(r4[1], tag), tagw(r4[2], tag), tagw(r4[3], tag));
                nxt = __shfl_sync(~0u, nxt, 0);
                if (nxt >= NT) break;
                tk = nxt;
            }
            STAMP(lane == 0, 16 + wi);
        }
    } else {
        float* red = (float*)(smem + SM_RED2);
        if (tid == 32) {
            const uint32_t ep0 = ld_relaxed32(&G.epoch.v);
            for (int e = 0; e < 8; e++) mbar_init(sb + SM_BAR + BAR_Q + e * 8, 1);
            for (int e = 1; e < 10; e++) mbar_init(sb + SM_BAR + BAR_W + e * 8, 1);
            mbar_init(sb + SM_BAR + BAR_BDONE, 1);
            mbar_init(sb + SM_BAR + BAR_PDONE, 1);
            mbar_init(sb + SM_BAR + BAR_QABS, 1);
            mbar_init(sb + SM_BAR + BAR_WFREE, 1);
            asm volatile("fence.mbarrier_init.release.cluster;" ::: "memory");
            asm volatile("st.volatile.shared.v4.u32 [%0], {%1, %2, %1, %1};" ::"r"(sb + SM_BAR + W_PROG), "r"(0), "r"(now_ns()) : "memory");
            *(volatile uint32_t*)(smem + SM_BAR + W_EPOCH) = ep0;
        } else if (tid == 64) {
            asm volatile("prefetch.tensormap [%0];" ::"l"(&M.m_v) : "memory");
            asm volatile("prefetch.tensormap [%0];" ::"l"(&M.m_wqB) : "memory");
            asm volatile("prefetch.tensormap [%0];" ::"l"(&M.m_wuk) : "memory");
        }
        __syncthreads();
        const uint32_t epoch = *(volatile uint32_t*)(smem + SM_BAR + W_EPOCH);
        const uint32_t tag = (epoch + 1) & 1;
        STAMP(tid == 0, 14);

        if (hasSlice) {
            const uint32_t nt = tag ^ 1;
            const int qoff = ((tid >> 5) & 1) * 4096 + 32 * j + (tid & 31);
            if (tid < 64) {
                st_relaxed32(G.qA + qoff, nt); st_relaxed32(G.qB + qoff, nt);
                if (tid < 32) {
                    st_relaxed32(G.o + 32 * j + tid, nt); st_relaxed32(G.o + 4096 + 32 * j + tid, nt);
                    st_relaxed32(G.ctx + 32 * j + tid, nt); st_relaxed32(G.ctx + 4096 + 32 * j + tid, nt);
                }
            }
            if (j == 0 && tid >= 64) st_relaxed32(&G.clk.v + (tid - 64), nt);
            if (tid >= 64 && tid < 72) st_relaxed32((uint32_t*)P.out + 8 * j + (tid - 64), 0);
            mbar_wait(sb + SM_BAR + BAR_W, 0);
            LAND(tid == 0, 17408 + 0 * 128 + j);
            STAMP(tid == 0, 15);
            uint2 bf[16];
            tall_prep(bf, sb + SM_P, warp, g, t);
            gemv_tall(sb + SM_WQ, bf, (float*)(smem + SM_RED1), warp, g, t);
            tall_finish((float*)(smem + SM_RED1), G.qA + qoff, tid, tag, 0, h >= HCLR ? 32 : 64);
            STAMP(tid == 0, 1);
            if (tid == 96) {
                mbar_expect_tx(sb + SM_BAR + BAR_W + 8, 32768);
                issue_tall(sb + SM_WQB, &M.m_wqB, j * 32, 0, sb + SM_BAR + BAR_W + 8, pol);
            }
            __syncwarp();
            tall_prep(bf, sb + SM_P + 2048, warp, g, t);
            mbar_wait(sb + SM_BAR + BAR_W + 8, 0);
            LAND(tid == 0, 17408 + 1 * 128 + j);
            gemv_tall(sb + SM_WQB, bf, red, warp, g, t);
            tall_finish(red, G.qB + qoff, tid, tag);
            if (tid == 96) {
                mbar_expect_tx(sb + SM_BAR + BAR_W + 16, 32768);
                tma_2d(sb + SM_WUK, &M.m_wuk, h * 128, qd * 128, sb + SM_BAR + BAR_W + 16, pol);
                mbar_arrive(sb + SM_BAR + BAR_WFREE);
            }
            STAMP(tid == 0, 25);
            named_bar(1, 128);
            uint4 qf[4];
            {
                const float* qp = G.qB + ((g & 1) * 32 + h) * 128 + t * 8;
                uint4 v[8];
                unsigned it = 0;
                while (true) {
                    uint32_t bad = 0;
#pragma unroll
                    for (int i = 0; i < 8; i++) v[i] = ld_relaxed128(qp + (i >> 1) * 32 + (i & 1) * 4);
#pragma unroll
                    for (int i = 0; i < 8; i++) bad |= bad4(v[i], tag);
                    if (!__any_sync(~0u, bad & 1u)) break;
                    __nanosleep(100);
                    if (++it > SPIN_LIMIT) __trap();
                }
#pragma unroll
                for (int s = 0; s < 4; s++)
                    qf[s] = make_uint4(pack_bf16(__uint_as_float(v[2 * s].x), __uint_as_float(v[2 * s].y)),
                                       pack_bf16(__uint_as_float(v[2 * s].z), __uint_as_float(v[2 * s].w)),
                                       pack_bf16(__uint_as_float(v[2 * s + 1].x), __uint_as_float(v[2 * s + 1].y)),
                                       pack_bf16(__uint_as_float(v[2 * s + 1].z), __uint_as_float(v[2 * s + 1].w)));
            }
            mbar_wait(sb + SM_BAR + BAR_W + 16, 0);
            LAND(tid == 0, 17408 + 2 * 128 + j);
#pragma unroll
            for (int jj = 0; jj < 2; jj++) {
                float c[4] = {0.f, 0.f, 0.f, 0.f};
#pragma unroll
                for (int s = 0; s < 4; s++) {
                    const uint32_t a = sb + SM_WUK + (32 * warp + 16 * jj + g) * 256 + (t + 4 * s) * 16;
                    const uint4 u = lds128(a), v = lds128(a + 2048);
                    mma16816(c, u.x, v.x, u.y, v.y, qf[s].x, qf[s].y);
                    mma16816(c, u.z, v.z, u.w, v.w, qf[s].z, qf[s].w);
                }
                const float val = (t & 2) ? ((t & 1) ? c[3] : c[2]) : ((t & 1) ? c[1] : c[0]);
                const int cc = 128 * qd + 32 * warp + 16 * jj + g + ((t & 2) ? 8 : 0);
                const int off = (cc >> 6) * 2048 + h * 64 + ((((cc & 63) >> 3) ^ (h & 7)) << 3) + (cc & 7);
                G.qabs[(t & 1) * 16384 + off] = __float2bfloat16(val);
            }
            named_bar(1, 128);
            if (tid == 0) red_release(&G.cntQabs.v);
            STAMP(tid == 0, 4);
            if (h >= HCLR) {
#pragma unroll
                for (int k = 0; k < 8; k++)
                    st_relaxed128(G.partO + (size_t)((32 + h) * 128 + 16 * k + (tid >> 3)) * 128 + qd * 32 + (tid & 7) * 4, nt, nt, nt, nt);
                if (tid < 64) st_relaxed128((char*)G.partML + ((32 + h) * 128 + qd * 32) * 32 + tid * 16, nt, nt, nt, nt);
                __threadfence();
                tall_finish((float*)(smem + SM_RED1), G.qA + qoff, tid, tag, 32, 64);
            }
        }

        if (isB) {
            const int ib = cta - NA_CTA;
            float acc[8][16];
#pragma unroll
            for (int i = 0; i < 8; i++)
#pragma unroll
                for (int k = 0; k < 16; k++) acc[i][k] = 0.f;
            float mrun[8], lrun[8];
#pragma unroll
            for (int i = 0; i < 8; i++) { mrun[i] = -INFINITY; lrun[i] = 0.f; }
            const uint64_t dQ = make_desc(sb + SM_SLOT + 5 * 32768);
            const uint64_t dP = make_desc(sb + SM_P);
            const uint32_t pst = sb + SM_P + (((lane >> 4) * 8 + (lane & 7)) * 128) + (((2 * warp + ((lane >> 3) & 1)) ^ (lane & 7)) << 4);
            mbar_wait(sb + SM_BAR + BAR_QABS, 0);
            STAMP(tid == 0, 5);
            int s0 = 0; uint32_t ph0 = 0;
            for (int it = 0; it < 16; it++) {
                int s1 = s0 + 1; uint32_t ph1 = ph0;
                if (s1 == 5) { s1 = 0; ph1 ^= 1; }
                const uint64_t dA0 = make_desc(sb + SM_SLOT + s0 * 32768), dA1 = make_desc(sb + SM_SLOT + s1 * 32768);
                float S[16];
                mbar_wait(sb + SM_BAR + BAR_BFULL + s0 * 8, ph0);
                mbar_wait(sb + SM_BAR + BAR_BFULL + s1 * 8, ph1);
                wg_fence();
#pragma unroll
                for (int k = 0; k < 32; k++) {
                    const uint64_t da = ((k < 16) ? dA0 : dA1) + (uint64_t)((((k >> 2) & 3) * 8192 + (k & 3) * 32) >> 4);
                    const uint64_t db = dQ + (uint64_t)(((k >> 2) * 4096 + (k & 3) * 32) >> 4);
                    wgmma_n32<0>(S, da, db, k > 0);
                }
                wg_commit();
                wg_wait<0>();
#pragma unroll
                for (int i = 0; i < 16; i++) S[i] *= SCALE;
                float mx[8];
#pragma unroll
                for (int i = 0; i < 8; i++) {
                    mx[i] = fmaxf(S[4 * (i >> 1) + (i & 1)], S[4 * (i >> 1) + 2 + (i & 1)]);
                    mx[i] = fmaxf(mx[i], __shfl_xor_sync(~0u, mx[i], 4));
                    mx[i] = fmaxf(mx[i], __shfl_xor_sync(~0u, mx[i], 8));
                    mx[i] = fmaxf(mx[i], __shfl_xor_sync(~0u, mx[i], 16));
                }
                if (g == 0) {
#pragma unroll
                    for (int jb = 0; jb < 4; jb++)
                        *(float2*)(red + warp * 32 + 8 * jb + 2 * t) = make_float2(mx[2 * jb], mx[2 * jb + 1]);
                }
                named_bar(1, 128);
                float al[8];
                bool chg = false;
                uint32_t R[8];
#pragma unroll
                for (int jb = 0; jb < 4; jb++) {
                    float2 a = *(float2*)(red + 8 * jb + 2 * t), b = *(float2*)(red + 32 + 8 * jb + 2 * t);
                    float2 c = *(float2*)(red + 64 + 8 * jb + 2 * t), d = *(float2*)(red + 96 + 8 * jb + 2 * t);
                    const float n0 = fmaxf(mrun[2 * jb], fmaxf(fmaxf(a.x, b.x), fmaxf(c.x, d.x)) * LOG2E);
                    const float n1 = fmaxf(mrun[2 * jb + 1], fmaxf(fmaxf(a.y, b.y), fmaxf(c.y, d.y)) * LOG2E);
                    chg |= (n0 != mrun[2 * jb]) | (n1 != mrun[2 * jb + 1]);
                    al[2 * jb] = ex2(mrun[2 * jb] - n0);
                    al[2 * jb + 1] = ex2(mrun[2 * jb + 1] - n1);
                    mrun[2 * jb] = n0; mrun[2 * jb + 1] = n1;
                    R[2 * jb]     = pack_bf16(ex2(fmaf(S[4 * jb], LOG2E, -n0)), ex2(fmaf(S[4 * jb + 1], LOG2E, -n1)));
                    R[2 * jb + 1] = pack_bf16(ex2(fmaf(S[4 * jb + 2], LOG2E, -n0)), ex2(fmaf(S[4 * jb + 3], LOG2E, -n1)));
                    lrun[2 * jb]     = fmaf(lrun[2 * jb], al[2 * jb], bf_lo(R[2 * jb]) + bf_lo(R[2 * jb + 1]));
                    lrun[2 * jb + 1] = fmaf(lrun[2 * jb + 1], al[2 * jb + 1], bf_hi(R[2 * jb]) + bf_hi(R[2 * jb + 1]));
                }
                asm volatile("stmatrix.sync.aligned.m8n8.x4.trans.shared.b16 [%0], {%1,%2,%3,%4};"
                             ::"r"(pst), "r"(R[0]), "r"(R[1]), "r"(R[2]), "r"(R[3]) : "memory");
                asm volatile("stmatrix.sync.aligned.m8n8.x4.trans.shared.b16 [%0], {%1,%2,%3,%4};"
                             ::"r"(pst + 2048), "r"(R[4]), "r"(R[5]), "r"(R[6]), "r"(R[7]) : "memory");
                asm volatile("fence.proxy.async.shared::cta;" ::: "memory");
                if (__any_sync(~0u, chg)) {
#pragma unroll
                    for (int mt = 0; mt < 8; mt++)
#pragma unroll
                        for (int k = 0; k < 16; k++) acc[mt][k] *= al[2 * (k >> 2) + (k & 1)];
                }
                named_bar(1, 128);
                wg_fence();
#pragma unroll
                for (int mt = 0; mt < 4; mt++)
#pragma unroll
                    for (int kk = 0; kk < 4; kk++)
                        wgmma_n32<1>(acc[mt], dA0 + (uint64_t)((mt * 8192 + kk * 2048) >> 4), dP + (uint64_t)((kk * 32) >> 4), 1);
                wg_commit();
#pragma unroll
                for (int mt = 0; mt < 4; mt++)
#pragma unroll
                    for (int kk = 0; kk < 4; kk++)
                        wgmma_n32<1>(acc[4 + mt], dA1 + (uint64_t)((mt * 8192 + kk * 2048) >> 4), dP + (uint64_t)((kk * 32) >> 4), 1);
                wg_commit();
                wg_wait<1>();
                if (lane == 0) mbar_arrive(sb + SM_BAR + BAR_BEMPTY + s0 * 8);
                wg_wait<0>();
                if (lane == 0) mbar_arrive(sb + SM_BAR + BAR_BEMPTY + s1 * 8);
                s0 = s1 + 1; ph0 = ph1;
                if (s0 == 5) { s0 = 0; ph0 ^= 1; }
            }
#pragma unroll
            for (int i = 0; i < 8; i++) {
                lrun[i] += __shfl_xor_sync(~0u, lrun[i], 4);
                lrun[i] += __shfl_xor_sync(~0u, lrun[i], 8);
                lrun[i] += __shfl_xor_sync(~0u, lrun[i], 16);
            }
            if (g == 0) {
#pragma unroll
                for (int jb = 0; jb < 4; jb++) {
                    *(float2*)(red + 128 + warp * 32 + 8 * jb + 2 * t) = make_float2(lrun[2 * jb], lrun[2 * jb + 1]);
                    if (warp == 0) *(float2*)(red + 256 + 8 * jb + 2 * t) = make_float2(mrun[2 * jb], mrun[2 * jb + 1]);
                }
            }
            named_bar(1, 128);
            if (tid == 0) mbar_arrive(sb + SM_BAR + BAR_BDONE);
            if (tid < 32)
                G.bml[ib * 32 + tid] = make_float2(red[256 + tid], red[128 + tid] + red[160 + tid] + red[192 + tid] + red[224 + tid]);
            float* bp = G.bpart + (size_t)ib * 16384 + (2 * t) * 512 + 16 * warp + g;
#pragma unroll
            for (int mt = 0; mt < 8; mt++)
#pragma unroll
                for (int k = 0; k < 16; k++)
                    bp[(8 * (k >> 2) + (k & 1)) * 512 + 64 * mt + ((k >> 1) & 1) * 8] = acc[mt][k];
            named_bar(1, 128);
            if (tid == 0) red_release(&G.cntB.v);
            STAMP(tid == 0, 6);
        }

        if (hasSlice) {
            if (tid == 0) {
                wait_prog(smem + SM_BAR + W_PROG, TUV);
                wait_counter(&G.cntB.v, (epoch + 1) * NB_CTA, 500);
                if (cta == 0) st_relaxed32(&G.epoch.v, epoch + 1);
                asm volatile("prefetch.tensormap [%0];" ::"l"(&M.m_uv[late]) : "memory");
                asm volatile("prefetch.tensormap [%0];" ::"l"(&M.m_w[mat]) : "memory");
            }
            named_bar(1, 128);
            if (tid == 32) mbar_arrive(sb + SM_BAR + BAR_PDONE);
            STAMP(tid == 0, 7);
            {
                const int b = tid >> 6, cp = tid & 63;
                uint2 ml[8];
#pragma unroll
                for (int i = 0; i < 8; i++) ml[i] = ld_relaxed64(G.bml + (b * 8 + i) * 32 + h);
                uint4 pv[2][8];
#pragma unroll
                for (int i = 0; i < 16; i++)
                    pv[i >> 3][i & 7] = ld_relaxed128(G.bpart + (size_t)(b * 8 + (i & 7)) * 16384 + h * 512 + (i >> 3) * 256 + 4 * cp);
                float M = __uint_as_float(ml[0].x);
#pragma unroll
                for (int i = 1; i < 8; i++) M = fmaxf(M, __uint_as_float(ml[i].x));
                float L = 0.f, wgt[8];
#pragma unroll
                for (int i = 0; i < 8; i++) {
                    wgt[i] = ex2(__uint_as_float(ml[i].x) - M);
                    L = fmaf(wgt[i], __uint_as_float(ml[i].y), L);
                }
                const float inv = 1.f / L;
#pragma unroll
                for (int x = 0; x < 2; x++) {
                    float v0 = 0.f, v1 = 0.f, v2 = 0.f, v3 = 0.f;
#pragma unroll
                    for (int i = 0; i < 8; i++) {
                        v0 = fmaf(wgt[i], __uint_as_float(pv[x][i].x), v0);
                        v1 = fmaf(wgt[i], __uint_as_float(pv[x][i].y), v1);
                        v2 = fmaf(wgt[i], __uint_as_float(pv[x][i].z), v2);
                        v3 = fmaf(wgt[i], __uint_as_float(pv[x][i].w), v3);
                    }
                    *(uint2*)(smem + SM_P + b * 1024 + x * 512 + cp * 8) = make_uint2(pack_bf16(v0 * inv, v1 * inv), pack_bf16(v2 * inv, v3 * inv));
                }
            }
            STAMP(tid == 0, 8);
        }
        {
            named_bar(1, 128);
#pragma unroll 1
            for (uint64_t plan = j < 64 ? 0xF7351260ull : (j < 124 ? (late ? 0xF75314260ull : 0xF7514603ull) : (hasSlice ? 0xF753426ull : 0xF10ull));
                 plan != 0xF; plan >>= 4) {
                const int step = plan & 15;
                if ((step & 14) == 4) {
                    const int hh = rg + 8 * warp;
                    const uint32_t real = step & 1, both = real & (mat | (warp != 3));
                    if (both) wait_ticket(smem + SM_BAR + W_PROG, mat ? NT + YB : min((33 + hh) * 128 + LAGT, NT + YLATE) + YX);
                    __syncwarp();
                    const float* src = (mat ? G.ctx : G.o) + hh * 128 + lane * 4;
                    uint4 v[2];
                    v[0] = v[1] = make_uint4(tag, tag, tag, tag);
                    uint32_t bad0 = real, bad1 = both;
                    unsigned it = 0;
                    while (true) {
                        ld_relaxed128_if(v[0], src, bad0);
                        ld_relaxed128_if(v[1], src + 4096, bad1);
                        bad0 = bad4(v[0], tag) & 1u; bad1 = bad4(v[1], tag) & 1u;
                        if (!__any_sync(~0u, bad0 | bad1)) break;
                        if (++it > SPIN_LIMIT) __trap();
                    }
#pragma unroll
                    for (int b = 0; b < 2; b++)
                        *(uint2*)(smem + SM_VEC + V_X + b * XSTR + (128 * warp + 4 * lane) * 2) =
                            make_uint2(pack_bf16(__uint_as_float(v[b].x), __uint_as_float(v[b].y)), pack_bf16(__uint_as_float(v[b].z), __uint_as_float(v[b].w)));
                    named_bar(1, 128);
                    STAMP(tid == 0, 29);
                } else if (step >= 6) {
                    const uint32_t real = step & 1;
                    const uint32_t xa = sb + SM_VEC + V_X + ((lane >> 1) & 1) * XSTR + 8 * (lane >> 3) * 2;
                    const uint32_t wa = sb + SM_SQ + 2 * 16384 + (8 * (lane >> 4) + (lane & 7)) * 128 +
                                        (((2 * warp + ((lane >> 3) & 1)) ^ (lane & 7)) << 4);
                    const uint32_t bs = sb + SM_BAR + BAR_S + 16;
                    const float* src = G.o + 4096 + (24 + rg) * 128 + lane * 4;
                    const uint32_t needx = real & (mat ^ 1);
                    uint32_t* dst = (uint32_t*)P.out + (t & 1) * 512 + mat * 256 + cg * 32 + warp * 8 + (t >> 1) * 4 + (g >> 1);
                    asm volatile("" : "+l"(dst));
                    uint4 v = make_uint4(tag, tag, tag, tag);
                    float d[4][4];
#pragma unroll
                    for (int i = 0; i < 16; i++) (&d[0][0])[i] = 0.f;
#pragma unroll 1
                    for (int u = 0; u < 3; u++) {
                        uint4 xf[4];
                        if (needx && u == 2) wait_ticket(smem + SM_BAR + W_PROG, NT + YP);
                        __syncwarp();
                        ld_relaxed128_if(v, src, needx & (u == 2));
#pragma unroll
                        for (int i = 0; i < 4; i++) xf[i] = ldsm4(xa + u * 256 + i * 64);
                        if (real) mbar_wait_nt(bs + u * 8, 0);
#pragma unroll
                        for (int i = 0; i < 4; i++) {
                            const uint4 w0 = ldsm4t(wa + u * 16384 + i * 4096), w1 = ldsm4t(wa + u * 16384 + i * 4096 + 2048);
                            mma16816(d[(i & 1) * 2], w0.x, w0.y, w0.z, w0.w, xf[i].x, xf[i].y);
                            mma16816(d[(i & 1) * 2 + 1], w1.x, w1.y, w1.z, w1.w, xf[i].z, xf[i].w);
                        }
                    }
                    unsigned it = 0;
                    while (__any_sync(~0u, bad4(v, tag) & 1u)) {
                        if (++it > SPIN_LIMIT) __trap();
                        v = ld_relaxed128(src);
                    }
                    STAMP(tid == 96, 20);
                    if (!mat)
                        *(uint2*)(smem + SM_VEC + V_X + XSTR + (384 + 4 * lane) * 2) =
                            make_uint2(pack_bf16(__uint_as_float(v.x), __uint_as_float(v.y)), pack_bf16(__uint_as_float(v.z), __uint_as_float(v.w)));
                    __syncwarp();
                    uint4 xf[4], w[4];
#pragma unroll
                    for (int i = 0; i < 4; i++) xf[i] = ldsm4(xa + 3 * 256 + i * 64);
#pragma unroll
                    for (int q = 0; q < 2; q++) {
                        if (q) {
#pragma unroll
                            for (int i = 0; i < 4; i++) {
                                d[0][i] = (d[0][i] + d[1][i]) + (d[2][i] + d[3][i]);
                                d[1][i] = d[2][i] = d[3][i] = 0.f;
                            }
                        }
                        if (real) mbar_wait_nt(bs + 24 + q * 8, 0);
#pragma unroll
                        for (int i = 0; i < 4; i++) w[i] = ldsm4t(wa + 3 * 16384 + q * 8192 + i * 2048);
#pragma unroll
                        for (int i = 0; i < 2; i++) {
                            mma16816(d[2 * i], w[2 * i].x, w[2 * i].y, w[2 * i].z, w[2 * i].w, xf[2 * q + i].x, xf[2 * q + i].y);
                            mma16816(d[2 * i + 1], w[2 * i + 1].x, w[2 * i + 1].y, w[2 * i + 1].z, w[2 * i + 1].w, xf[2 * q + i].z, xf[2 * q + i].w);
                        }
                    }
                    STAMP(tid == 64, 22);
                    float e[4];
#pragma unroll
                    for (int i = 0; i < 4; i++) e[i] = (t & 2) ? d[i][2] : d[i][0];
                    red_out(dst, ((e[0] + e[1]) + e[2]) + e[3], g, real);
                    STAMP(tid == 64, 13);
                    if (real) asm volatile("exit;");
                } else if (step >= 2) {
                    uint2 bf[16];
                    tall_prep(bf, sb + SM_P, warp, g, t);
                    if (step & 1) mbar_wait(sb + SM_BAR + BAR_S + (warp >> 1) * 8, 0);
                    LAND(tid == 64, 17408 + 3 * 128 + j);
                    gemv_tall(sb + SM_SQ, bf, red + 512, warp, g, t);
                    tall_finish(red + 512, G.ctx + ((tid >> 5) & 1) * 4096 + 32 * j + (tid & 31), tid, tag, 0, (step & 1) ? 64 : 0);
                    STAMP(tid == 0, 12);
                } else {
                    const int b = step;
                    const int hm = min(h, 31), bh = 32 * b + hm;
                    wait_ticket(smem + SM_BAR + W_PROG, min((bh + 1) * 128 + LAGT, NT + YLATE + max(hm - 27, 0) * YSL));
                    __syncwarp();
                    float* rb = red + b * 256;
                    combineA(G, bh, qd, tag, rb, tid, smem + SM_BAR + W_PROG);
                    {
                        if (tid < 32)
                            st_relaxed32(G.o + bh * 128 + 32 * qd + tid, tagw((rb[tid] + rb[32 + tid]) + (rb[64 + tid] + rb[96 + tid]), tag));
                        STAMP(tid == 0, 9 + 2 * b);
                    }
                }
            }
        }
    }
}

typedef CUresult (*EncodeFn)(CUtensorMap*, CUtensorMapDataType, cuuint32_t, void*, const cuuint64_t*, const cuuint64_t*,
                             const cuuint32_t*, const cuuint32_t*, CUtensorMapInterleave, CUtensorMapSwizzle,
                             CUtensorMapL2promotion, CUtensorMapFloatOOBfill);

}

extern "C" void kernel_launch(void* const* d_in, const int* in_sizes, int n_in, void* d_out, int out_size) {
    (void)in_sizes; (void)n_in; (void)out_size;
    static EncodeFn encode = nullptr;
    static void* scratch = nullptr;
    if (!encode) {
        void* fn = nullptr;
        cudaDriverEntryPointQueryResult st;
        cudaGetDriverEntryPoint("cuTensorMapEncodeTiled", &fn, cudaEnableDefault, &st);
        encode = (EncodeFn)fn;
        cudaGetSymbolAddress(&scratch, g_raw);
        cudaFuncSetAttribute(fused_decode_kernel, cudaFuncAttributeMaxDynamicSharedMemorySize, SM_TOTAL);
    }
    Ptrs P;
    Maps M;
    auto mk = [&](CUtensorMap* m, void* ptr, cuuint64_t cols, cuuint64_t rows, cuuint32_t bc, cuuint32_t br, CUtensorMapSwizzle sw,
                  CUtensorMapL2promotion promo) {
        const cuuint64_t gdim[2] = {cols, rows};
        const cuuint64_t gstr[1] = {cols * 2};
        const cuuint32_t box[2] = {bc, br};
        const cuuint32_t estr[2] = {1, 1};
        encode(m, CU_TENSOR_MAP_DATA_TYPE_BFLOAT16, 2, ptr, gdim, gstr, box, estr, CU_TENSOR_MAP_INTERLEAVE_NONE, sw,
               promo, CU_TENSOR_MAP_FLOAT_OOB_FILL_NONE);
    };
    mk(&M.m_wq, d_in[3], 4096, 512, 32, 256, CU_TENSOR_MAP_SWIZZLE_64B, CU_TENSOR_MAP_L2_PROMOTION_NONE);
    auto mk3 = [&](CUtensorMap* m, void* ptr, cuuint64_t cols, cuuint64_t rows) {
        const cuuint64_t gdim[3] = {64, rows, cols / 64};
        const cuuint64_t gstr[2] = {cols * 2, 128};
        const cuuint32_t box[3] = {64, 64, 2};
        const cuuint32_t estr[3] = {1, 1, 1};
        encode(m, CU_TENSOR_MAP_DATA_TYPE_BFLOAT16, 3, ptr, gdim, gstr, box, estr, CU_TENSOR_MAP_INTERLEAVE_NONE,
               CU_TENSOR_MAP_SWIZZLE_128B, CU_TENSOR_MAP_L2_PROMOTION_L2_256B, CU_TENSOR_MAP_FLOAT_OOB_FILL_NONE);
    };
    mk3(&M.m_v, d_in[2], 128, 524288);
    mk(&M.m_uv[0], d_in[9], 4096, 512, 32, 128, CU_TENSOR_MAP_SWIZZLE_64B, CU_TENSOR_MAP_L2_PROMOTION_NONE);
    mk(&M.m_uv[1], d_in[9], 4096, 512, 32, 128, CU_TENSOR_MAP_SWIZZLE_64B, CU_TENSOR_MAP_L2_PROMOTION_L2_256B);
    mk(&M.m_w[0], d_in[4], 512, 4096, 64, 64, CU_TENSOR_MAP_SWIZZLE_128B, CU_TENSOR_MAP_L2_PROMOTION_L2_256B);
    mk(&M.m_w[1], d_in[10], 512, 4096, 64, 64, CU_TENSOR_MAP_SWIZZLE_128B, CU_TENSOR_MAP_L2_PROMOTION_L2_256B);
    mk(&M.m_ckv, d_in[6], 512, 16384, 64, 64, CU_TENSOR_MAP_SWIZZLE_128B, CU_TENSOR_MAP_L2_PROMOTION_L2_256B);
    mk(&M.m_wqB, d_in[7], 4096, 512, 32, 256, CU_TENSOR_MAP_SWIZZLE_64B, CU_TENSOR_MAP_L2_PROMOTION_NONE);
    mk(&M.m_wuk, d_in[8], 4096, 512, 128, 128, CU_TENSOR_MAP_SWIZZLE_NONE, CU_TENSOR_MAP_L2_PROMOTION_L2_256B);
    P.xA = (const __nv_bfloat16*)d_in[0];
    P.K = (const __nv_bfloat16*)d_in[1];
    P.xB = (const __nv_bfloat16*)d_in[5];
    P.out = (__nv_bfloat16*)d_out;
    P.g = (Scratch*)scratch;
    cudaLaunchConfig_t cfg = {};
    cfg.gridDim = dim3(GRID);
    cfg.blockDim = dim3(NTHREADS);
    cfg.dynamicSmemBytes = SM_TOTAL;
    cfg.stream = cudaStreamPerThread;
    cudaLaunchAttribute attr;
    attr.id = cudaLaunchAttributeCooperative;
    attr.val.cooperative = 1;
    cfg.attrs = &attr;
    cfg.numAttrs = 1;
    cudaLaunchKernelEx(&cfg, fused_decode_kernel, P, M);
}
```

```cpp
#include <cuda_runtime.h>
#include <cuda_bf16.h>
#include <cuda.h>
#include <stdint.h>

namespace {

constexpr int NT       = 8192;
constexpr int GRID     = 132;
constexpr int NB_CTA   = 16;
constexpr int NA_CTA   = GRID - NB_CTA;
constexpr int NWORK    = 3;
#define YV 292
#define DV 54
#define YW 407
#define DW 68
#define DL 6
#define YX 150
#define YB 582
#define YP 605
#define XRV 330
#define TV 3200
#define PFB 16384
#define LAGT 1060
#define YLATE 120
#define YSL 70
#define YO 450
#define YOS 40
#define TUV (47 * 128)
#define XPK 80
#define FRZ 400
#define GLOOK 120
#define GL2 70
#define BIAS2 215
#define THR2 350
#define QDELAY 1300
constexpr int NEARX = 400;
constexpr int GN = 8, GST = 16, GX = 512;
constexpr int JE0   = 112;
constexpr int HCLR  = 26;
constexpr int BINFL = 2;
constexpr int NSTATIC  = NA_CTA * (NWORK + 1);
constexpr unsigned DRAWS = (NT - NSTATIC) + GRID * NWORK;
static_assert(52 * 128 + LAGT + 300 <= NT && TUV + 10 * 128 <= NT, "wait_prog thresholds must be reachable");
static_assert(GX - FRZ < GRID * NWORK && GX / GST + GN <= 64, "every clock sample must be drawn and fit");
constexpr int NTHREADS = 256;
constexpr float SCALE = 0.08838834764831845f, LOG2E = 1.4426950408889634f;
constexpr unsigned SPIN_LIMIT = 1u << 22;

constexpr int SM_SLOT  = 0;
constexpr int SM_QA    = 196608;
constexpr int SM_P     = SM_QA + 16384;
constexpr int SM_RED1  = SM_P + 4096;
constexpr int SM_RED2  = SM_RED1 + 2048;
constexpr int SM_VEC   = SM_RED2 + 4096;
constexpr int SM_BAR   = SM_VEC + 3072;
constexpr int SM_TOTAL = SM_BAR + 352;
constexpr int V_X    = 512;
constexpr int BAR_FULL = 0;
constexpr int BAR_PDONE= 48;
constexpr int BAR_BDONE= 56;
constexpr int BAR_X    = 64;
constexpr int BAR_QABS = 72;
constexpr int BAR_BFULL= 80;
constexpr int BAR_BEMPTY=120;
constexpr int BAR_WFREE= 160;
constexpr int BAR_W    = 168;
constexpr int BAR_S    = 192;
constexpr int BAR_Q    = 264;
constexpr int W_EPOCH  = 328;
constexpr int W_PROG   = 336;
constexpr int SM_WQ = 3 * 32768, SM_WQB = 4 * 32768, SM_WUK = 5 * 32768;
constexpr int SM_SQ = 3 * 32768;
constexpr int XSTR = 1024 + 16;

struct __align__(128) Cnt { unsigned v; unsigned pad[31]; };
struct __align__(128) Scratch {
    Cnt epoch, ticket, cntQabs, cntB;
    float qA[64 * 128], qB[64 * 128];
    __nv_bfloat16 qabs[2 * 32 * 512];
    float  partO[NT * 128];
    float2 partML[NT * 4];
    float  bpart[NB_CTA * 32 * 512];
    float2 bml[NB_CTA * 32];
    float  ctx[32 * 4 * 2 * 128];
    float  o[2 * 4096];
    Cnt    clk, clk1;
};
__device__ __align__(128) unsigned char g_raw[sizeof(Scratch)];

__device__ __forceinline__ int slice_of(int cta) {
    return cta >= 128 ? cta : ((cta & 8) << 3) | ((cta >> 4) << 3) | (cta & 7);
}

#define STAMP(cond, i) do {} while (0)
#define LAND(cond, i) do {} while (0)

__device__ __forceinline__ void mbar_init(uint32_t bar, int cnt) {
    asm volatile("mbarrier.init.shared::cta.b64 [%0], %1;" ::"r"(bar), "r"(cnt) : "memory");
}
__device__ __forceinline__ void mbar_expect_tx(uint32_t bar, uint32_t bytes) {
    asm volatile("mbarrier.arrive.expect_tx.shared::cta.b64 _, [%0], %1;" ::"r"(bar), "r"(bytes) : "memory");
}
__device__ __forceinline__ void mbar_arrive(uint32_t bar) {
    asm volatile("mbarrier.arrive.shared::cta.b64 _, [%0];" ::"r"(bar) : "memory");
}
__device__ __forceinline__ void mbar_wait(uint32_t bar, uint32_t parity) {
    unsigned it = 0;
    while (true) {
        uint32_t ok;
        asm volatile("{\n.reg .pred p;\nmbarrier.try_wait.parity.shared::cta.b64 p, [%1], %2;\nselp.u32 %0, 1, 0, p;\n}\n"
                     : "=r"(ok) : "r"(bar), "r"(parity) : "memory");
        if (ok) break;
        if (++it > SPIN_LIMIT) __trap();
    }
}
__device__ __forceinline__ void mbar_wait_nt(uint32_t bar, uint32_t parity) {
#pragma unroll 1
    for (unsigned it = 0; it < SPIN_LIMIT; it++) {
        uint32_t ok;
        asm volatile("{\n.reg .pred p;\nmbarrier.try_wait.parity.shared::cta.b64 p, [%1], %2;\nselp.u32 %0, 1, 0, p;\n}\n"
                     : "=r"(ok) : "r"(bar), "r"(parity) : "memory");
        if (ok) break;
    }
}
__device__ __forceinline__ bool mbar_test(uint32_t bar, uint32_t parity) {
    uint32_t ok;
    asm volatile("{\n.reg .pred p;\nmbarrier.test_wait.parity.shared::cta.b64 p, [%1], %2;\nselp.u32 %0, 1, 0, p;\n}\n"
                 : "=r"(ok) : "r"(bar), "r"(parity) : "memory");
    return ok;
}
__device__ __forceinline__ void bulk_load(uint32_t dst, const void* src, uint32_t bytes, uint32_t bar, uint64_t pol) {
    asm volatile("cp.async.bulk.shared::cluster.global.mbarrier::complete_tx::bytes.L2::cache_hint [%0], [%1], %2, [%3], %4;"
                 ::"r"(dst), "l"(src), "r"(bytes), "r"(bar), "l"(pol) : "memory");
}
__device__ __forceinline__ void bulk_load_nohint(uint32_t dst, const void* src, uint32_t bytes, uint32_t bar) {
    asm volatile("cp.async.bulk.shared::cluster.global.mbarrier::complete_tx::bytes [%0], [%1], %2, [%3];"
                 ::"r"(dst), "l"(src), "r"(bytes), "r"(bar) : "memory");
}
__device__ __forceinline__ void tma_2d(uint32_t dst, const CUtensorMap* map, int c0, int c1, uint32_t bar, uint64_t pol) {
    asm volatile("cp.async.bulk.tensor.2d.shared::cluster.global.mbarrier::complete_tx::bytes.L2::cache_hint [%0], [%1, {%3, %4}], [%2], %5;"
                 ::"r"(dst), "l"(map), "r"(bar), "r"(c0), "r"(c1), "l"(pol) : "memory");
}
__device__ __forceinline__ void tma_3d(uint32_t dst, const CUtensorMap* map, int c1, int c2, uint32_t bar, uint64_t pol) {
    asm volatile("cp.async.bulk.tensor.3d.shared::cluster.global.mbarrier::complete_tx::bytes.L2::cache_hint [%0], [%1, {%3, %4, %5}], [%2], %6;"
                 ::"r"(dst), "l"(map), "r"(bar), "r"(0), "r"(c1), "r"(c2), "l"(pol) : "memory");
}
__device__ __forceinline__ void wait_prog(const unsigned char* smem_word, unsigned th) {
    unsigned it = 0;
    while (*(volatile const unsigned*)(smem_word + 8) + NSTATIC < th) {
        __nanosleep(60);
        if (++it > SPIN_LIMIT) __trap();
    }
}
__device__ __forceinline__ uint32_t now_ns() {
    uint32_t t;
    asm volatile("mov.u32 %0, %globaltimer_lo;" : "=r"(t) :: "memory");
    return t;
}
__device__ __forceinline__ void note_draw(unsigned char* smem_word, unsigned raw, unsigned* clk, uint32_t tag) {
    const uint32_t a = (uint32_t)__cvta_generic_to_shared(smem_word);
    asm volatile("st.volatile.u32 [%0], %1;" ::"l"(smem_word + 8), "r"(raw) : "memory");
    const uint32_t now = now_ns();
    if ((int)raw < NT - NSTATIC - FRZ) asm volatile("st.volatile.shared.v2.u32 [%0], {%1, %2};" ::"r"(a), "r"(raw), "r"(now) : "memory");
    const unsigned q = NT - NSTATIC - FRZ + GX - raw;
    if ((q & ~((GN - 1) * GST | GX)) == 0)
        asm volatile("st.relaxed.gpu.global.u32 [%0], %1;" ::"l"(clk + q / GST), "r"(((now + (q - GX) * 10) & ~1u) | tag) : "memory");
}
__device__ __forceinline__ void wait_ticket(const unsigned char* smem_word, int th) {
    wait_prog(smem_word, min(th, NT - NEARX));
    uint32_t tk, t0;
#pragma unroll 1
    for (unsigned it = 0; it < SPIN_LIMIT; it++) {
        asm volatile("ld.volatile.shared.v2.u32 {%0, %1}, [%2];" : "=r"(tk), "=r"(t0) : "r"((uint32_t)__cvta_generic_to_shared(smem_word)) : "memory");
        if ((int)(now_ns() - t0) >= (th - NSTATIC - (int)tk) * 10) break;
        __nanosleep(20);
    }
}
__device__ __forceinline__ bool mbar_wait_for(uint32_t bar, uint32_t parity, int n) {
    uint32_t c0, c;
    asm volatile("mov.u32 %0, %%clock;" : "=r"(c0) :: "memory");
    do {
        if (mbar_test(bar, parity)) return true;
        asm volatile("mov.u32 %0, %%clock;" : "=r"(c) :: "memory");
    } while ((int)(c - c0) < n);
    return false;
}
__device__ __forceinline__ bool elect_one() {
    uint32_t p;
    asm volatile("{\n.reg .pred p;\nelect.sync _|p, 0xffffffff;\nselp.u32 %0, 1, 0, p;\n}\n" : "=r"(p));
    return p;
}
__device__ __forceinline__ void fence_proxy_async() { asm volatile("fence.proxy.async;" ::: "memory"); }
__device__ __forceinline__ void named_bar(int id, int n) { asm volatile("bar.sync %0, %1;" ::"r"(id), "r"(n) : "memory"); }

__device__ __forceinline__ uint4 lds128(uint32_t a) {
    uint4 v;
    asm volatile("ld.shared.v4.u32 {%0,%1,%2,%3}, [%4];" : "=r"(v.x), "=r"(v.y), "=r"(v.z), "=r"(v.w) : "r"(a));
    return v;
}
__device__ __forceinline__ uint4 ldsm4(uint32_t a) {
    uint4 v;
    asm volatile("ldmatrix.sync.aligned.m8n8.x4.shared.b16 {%0,%1,%2,%3}, [%4];" : "=r"(v.x), "=r"(v.y), "=r"(v.z), "=r"(v.w) : "r"(a));
    return v;
}
__device__ __forceinline__ uint4 ldsm4t(uint32_t a) {
    uint4 v;
    asm volatile("ldmatrix.sync.aligned.m8n8.x4.trans.shared.b16 {%0,%1,%2,%3}, [%4];" : "=r"(v.x), "=r"(v.y), "=r"(v.z), "=r"(v.w) : "r"(a));
    return v;
}
__device__ __forceinline__ uint2 lds64(uint32_t a) {
    uint2 v;
    asm volatile("ld.shared.v2.u32 {%0,%1}, [%2];" : "=r"(v.x), "=r"(v.y) : "r"(a));
    return v;
}
__device__ __forceinline__ uint4 ld_relaxed128(const void* p) {
    uint4 v;
    asm volatile("ld.relaxed.gpu.global.v4.u32 {%0,%1,%2,%3}, [%4];" : "=r"(v.x), "=r"(v.y), "=r"(v.z), "=r"(v.w) : "l"(p) : "memory");
    return v;
}
__device__ __forceinline__ uint2 ld_relaxed64(const void* p) {
    uint2 v;
    asm volatile("ld.relaxed.gpu.global.v2.u32 {%0,%1}, [%2];" : "=r"(v.x), "=r"(v.y) : "l"(p) : "memory");
    return v;
}
__device__ __forceinline__ uint32_t ld_relaxed32(const void* p) {
    uint32_t v;
    asm volatile("ld.relaxed.gpu.global.u32 %0, [%1];" : "=r"(v) : "l"(p) : "memory");
    return v;
}
__device__ __forceinline__ uint32_t ld_acquire32(const void* p) {
    uint32_t v;
    asm volatile("ld.acquire.gpu.global.u32 %0, [%1];" : "=r"(v) : "l"(p) : "memory");
    return v;
}
__device__ __forceinline__ void st_relaxed128(void* p, uint32_t a, uint32_t b, uint32_t c, uint32_t d) {
    asm volatile("st.relaxed.gpu.global.v4.u32 [%0], {%1,%2,%3,%4};" ::"l"(p), "r"(a), "r"(b), "r"(c), "r"(d) : "memory");
}
__device__ __forceinline__ void red_release(unsigned* p) {
    asm volatile("red.release.gpu.global.add.u32 [%0], 1;" ::"l"(p) : "memory");
}
__device__ __forceinline__ void wait_counter(const unsigned* p, unsigned target, unsigned ns) {
    unsigned it = 0;
    while ((int)(ld_acquire32(p) - target) < 0) {
        __nanosleep(ns);
        if (++it > SPIN_LIMIT) __trap();
    }
}
__device__ __forceinline__ uint32_t prmt(uint32_t a, uint32_t b, uint32_t s) {
    uint32_t d;
    asm("prmt.b32 %0, %1, %2, %3;" : "=r"(d) : "r"(a), "r"(b), "r"(s));
    return d;
}
__device__ __forceinline__ uint32_t pack_bf16(float lo, float hi) {
    uint32_t d;
    asm("cvt.rn.bf16x2.f32 %0, %1, %2;" : "=r"(d) : "f"(hi), "f"(lo));
    return d;
}
__device__ __forceinline__ float ex2(float x) {
    float y;
    asm("ex2.approx.ftz.f32 %0, %1;" : "=f"(y) : "f"(x));
    return y;
}
__device__ __forceinline__ float bf_lo(uint32_t v) { return __uint_as_float(v << 16); }
__device__ __forceinline__ float bf_hi(uint32_t v) { return __uint_as_float(v & 0xffff0000u); }
__device__ __forceinline__ void scale_scores(float& a, float& b) {
    uint32_t p = pack_bf16(a, b);
    p = pack_bf16(bf_lo(p) * SCALE, bf_hi(p) * SCALE);
    a = bf_lo(p); b = bf_hi(p);
}
__device__ __forceinline__ uint32_t tagw(float v, uint32_t tag) {
    uint32_t d;
    asm("lop3.b32 %0, %1, 0xfffffffe, %2, 0xEA;" : "=r"(d) : "r"(__float_as_uint(v)), "r"(tag));
    return d;
}
__device__ __forceinline__ uint32_t bad2(uint32_t x, uint32_t y, uint32_t tag) {
    uint32_t d;
    asm("lop3.b32 %0, %1, %2, %3, 0x7E;" : "=r"(d) : "r"(x), "r"(y), "r"(tag));
    return d;
}
__device__ __forceinline__ uint32_t bad4(const uint4& v, uint32_t tag) { return bad2(v.x, v.y, tag) | bad2(v.z, v.w, tag); }
__device__ __forceinline__ void ld_relaxed128_if(uint4& v, const void* p, uint32_t c) {
    asm volatile("{\n.reg .pred p;\nsetp.ne.u32 p, %5, 0;\n@p ld.relaxed.gpu.global.v4.u32 {%0,%1,%2,%3}, [%4];\n}\n"
                 : "+r"(v.x), "+r"(v.y), "+r"(v.z), "+r"(v.w) : "l"(p), "r"(c) : "memory");
}
__device__ __forceinline__ void ld_relaxed64_if(uint2& v, const void* p, uint32_t c) {
    asm volatile("{\n.reg .pred p;\nsetp.ne.u32 p, %3, 0;\n@p ld.relaxed.gpu.global.v2.u32 {%0,%1}, [%2];\n}\n"
                 : "+r"(v.x), "+r"(v.y) : "l"(p), "r"(c) : "memory");
}
__device__ __forceinline__ void st_relaxed32(void* p, uint32_t a) {
    asm volatile("st.relaxed.gpu.global.u32 [%0], %1;" ::"l"(p), "r"(a) : "memory");
}
__device__ __forceinline__ void red_out(uint32_t* word, float v, int col, uint32_t go) {
    const uint32_t pk = (col & 1) ? pack_bf16(-0.f, v) : pack_bf16(v, -0.f);
    asm volatile("{\n.reg .pred p;\nsetp.ne.u32 p, %2, 0;\n@p red.relaxed.gpu.global.add.noftz.bf16x2 [%0], %1;\n}\n"
                 ::"l"(word), "r"(pk), "r"(go) : "memory");
}
__device__ __forceinline__ void mma16816(float (&c)[4], uint32_t a0, uint32_t a1, uint32_t a2, uint32_t a3,
                                         uint32_t b0, uint32_t b1) {
    asm("mma.sync.aligned.m16n8k16.row.col.f32.bf16.bf16.f32 {%0,%1,%2,%3}, {%4,%5,%6,%7}, {%8,%9}, {%0,%1,%2,%3};"
        : "+f"(c[0]), "+f"(c[1]), "+f"(c[2]), "+f"(c[3])
        : "r"(a0), "r"(a1), "r"(a2), "r"(a3), "r"(b0), "r"(b1));
}
__device__ __forceinline__ uint64_t make_desc(uint32_t addr) {
    return (uint64_t)((addr & 0x3FFFF) >> 4) | ((uint64_t)1 << 16) | ((uint64_t)64 << 32) | ((uint64_t)1 << 62);
}
template <int TRANS_A>
__device__ __forceinline__ void wgmma_n32(float (&d)[16], uint64_t da, uint64_t db, int scale_d) {
    asm volatile("{\n.reg .pred p;\nsetp.ne.b32 p, %18, 0;\n"
                 "wgmma.mma_async.sync.aligned.m64n32k16.f32.bf16.bf16 "
                 "{%0,%1,%2,%3,%4,%5,%6,%7,%8,%9,%10,%11,%12,%13,%14,%15}, %16, %17, p, 1, 1, %19, 0;\n}\n"
                 : "+f"(d[0]), "+f"(d[1]), "+f"(d[2]), "+f"(d[3]), "+f"(d[4]), "+f"(d[5]), "+f"(d[6]), "+f"(d[7]),
                   "+f"(d[8]), "+f"(d[9]), "+f"(d[10]), "+f"(d[11]), "+f"(d[12]), "+f"(d[13]), "+f"(d[14]), "+f"(d[15])
                 : "l"(da), "l"(db), "r"(scale_d), "n"(TRANS_A));
}
__device__ __forceinline__ void wg_fence()  { asm volatile("wgmma.fence.sync.aligned;" ::: "memory"); }
__device__ __forceinline__ void wg_commit() { asm volatile("wgmma.commit_group.sync.aligned;" ::: "memory"); }
template <int N> __device__ __forceinline__ void wg_wait() { asm volatile("wgmma.wait_group.sync.aligned %0;" ::"n"(N) : "memory"); }

__device__ __forceinline__ void issue_tall(uint32_t dst, const CUtensorMap* map, int col, int row, uint32_t bar, uint64_t pol) {
    tma_2d(dst, map, col, row, bar, pol);
    tma_2d(dst + 16384, map, col, row + 256, bar, pol);
}
__device__ __forceinline__ void tall_prep(uint2 (&bf)[16], uint32_t xbase, int w4, int g, int t) {
    const uint32_t xp = xbase + ((g >> 1) & 1) * 1024 + w4 * 256 + (t >> 1) * 8;
    const uint32_t sel = (g & 1) ? ((t & 1) ? 0x3244u : 0x1044u) : ((t & 1) ? 0x4432u : 0x4410u);
#pragma unroll
    for (int i = 0; i < 16; i++) {
        const uint2 xw = lds64(xp + i * 16);
        bf[i] = make_uint2(prmt(xw.x, 0, sel), prmt(xw.y, 0, sel));
    }
}
__device__ __forceinline__ void gemv_tall(uint32_t wbase, const uint2 (&bf)[16], float* red, int w4, int g, int t) {
    const uint32_t wu = wbase + (128 * w4 + (t & 1) + 4 * (t >> 1)) * 64 + (((g >> 1) ^ (t & 2)) << 4) + (g & 1) * 8;
    const uint32_t wv = (wu + 128) ^ 16;
    float a[4][4];
#pragma unroll
    for (int i = 0; i < 16; i++) (&a[0][0])[i] = 0.f;
#pragma unroll
    for (int i = 0; i < 16; i++) {
        const uint2 u = lds64(wu + i * 512), v = lds64(wv + i * 512);
        mma16816(a[i & 3], u.x, u.y, v.x, v.y, bf[i].x, bf[i].y);
    }
    if (t < 2)
        *(float4*)(red + (w4 * 2 + t) * 32 + 4 * g) =
            make_float4((a[0][0] + a[1][0]) + (a[2][0] + a[3][0]), (a[0][1] + a[1][1]) + (a[2][1] + a[3][1]),
                        (a[0][2] + a[1][2]) + (a[2][2] + a[3][2]), (a[0][3] + a[1][3]) + (a[2][3] + a[3][3]));
}
__device__ __forceinline__ void tall_finish(const float* red, float* dst, int tid, uint32_t tag, int lo = 0, int hi = 64) {
    named_bar(1, 128);
    if (tid >= lo && tid < hi) {
        st_relaxed32(dst, tagw((red[tid] + red[64 + tid]) + (red[128 + tid] + red[192 + tid]), tag));
    }
}

__device__ __forceinline__ void combineA(Scratch& G, int bh, int dq, uint32_t tag, float* red, int tid, const unsigned char* prog) {
    const int r = tid >> 3, c4 = tid & 7, w4 = tid >> 5, lane = tid & 31;
    const float2* ml = G.partML + (bh * 128 + r) * 4;
    const float* po = G.partO + (size_t)(bh * 128 + r) * 128 + dq * 32 + c4 * 4;
    uint2 m[8];
    uint4 o[8];
    uint32_t bad[8];
    STAMP(tid == 0 && bh >= 32, 28);
#pragma unroll
    for (int k = 0; k < 8; k++) m[k] = ld_relaxed64(ml + 64 * k);
#pragma unroll
    for (int k = 0; k < 8; k++) {
        o[k] = make_uint4(~tag, ~tag, ~tag, ~tag);
        ld_relaxed128_if(o[k], po + (size_t)k * 16 * 128, bh < 60);
    }
    unsigned it = 0;
    while (true) {
        uint32_t any = 0;
#pragma unroll
        for (int k = 0; k < 8; k++) { bad[k] = bad2(m[k].x, m[k].y, tag) & 1u; any |= bad[k]; }
        if (!__any_sync(~0u, any)) break;
#pragma unroll
        for (int k = 0; k < 8; k++) ld_relaxed64_if(m[k], ml + 64 * k, bad[k]);
        if (++it > SPIN_LIMIT) __trap();
    }
    STAMP(tid == 0 && bh >= 32, 30);
    STAMP(tid == 0 && bh >= 32, 19);
    float M = fmaxf(fmaxf(fmaxf(__uint_as_float(m[0].x), __uint_as_float(m[1].x)), fmaxf(__uint_as_float(m[2].x), __uint_as_float(m[3].x))),
                    fmaxf(fmaxf(__uint_as_float(m[4].x), __uint_as_float(m[5].x)), fmaxf(__uint_as_float(m[6].x), __uint_as_float(m[7].x))));
    M = fmaxf(M, __shfl_xor_sync(~0u, M, 8));
    M = fmaxf(M, __shfl_xor_sync(~0u, M, 16));
    float wgt[8], L = 0.f;
#pragma unroll
    for (int k = 0; k < 8; k++) {
        wgt[k] = ex2(__uint_as_float(m[k].x) - M);
        L = fmaf(wgt[k], __uint_as_float(m[k].y), L);
    }
    L += __shfl_xor_sync(~0u, L, 8);
    L += __shfl_xor_sync(~0u, L, 16);
    if (lane == 0) { red[128 + w4] = M; red[132 + w4] = L; }
    named_bar(1, 128);
    {
        const float4 Mw = *(float4*)(red + 128), Lw = *(float4*)(red + 132);
        const float Mx = fmaxf(fmaxf(Mw.x, Mw.y), fmaxf(Mw.z, Mw.w));
        const float Lt = (ex2(Mw.x - Mx) * Lw.x + ex2(Mw.y - Mx) * Lw.y) + (ex2(Mw.z - Mx) * Lw.z + ex2(Mw.w - Mx) * Lw.w);
        const float f = ex2(M - Mx) / Lt;
#pragma unroll
        for (int k = 0; k < 8; k++) wgt[k] *= f;
    }
    STAMP(tid == 0 && bh >= 32, 23);
    if (bh >= 60) wait_ticket(prog, NT + YO + (bh - 63) * YOS);
    while (true) {
        uint32_t any = 0;
#pragma unroll
        for (int k = 0; k < 8; k++) { bad[k] = bad4(o[k], tag) & 1u; any |= bad[k]; }
        if (!__any_sync(~0u, any)) break;
#pragma unroll
        for (int k = 0; k < 8; k++) ld_relaxed128_if(o[k], po + (size_t)k * 16 * 128, bad[k]);
        if (++it > SPIN_LIMIT) __trap();
    }
    STAMP(tid == 0 && bh >= 32, 31);
    float a0 = 0.f, a1 = 0.f, a2 = 0.f, a3 = 0.f, b0 = 0.f, b1 = 0.f, b2 = 0.f, b3 = 0.f;
#pragma unroll
    for (int k = 0; k < 8; k += 2) {
        a0 = fmaf(wgt[k], __uint_as_float(o[k].x), a0); b0 = fmaf(wgt[k + 1], __uint_as_float(o[k + 1].x), b0);
        a1 = fmaf(wgt[k], __uint_as_float(o[k].y), a1); b1 = fmaf(wgt[k + 1], __uint_as_float(o[k + 1].y), b1);
        a2 = fmaf(wgt[k], __uint_as_float(o[k].z), a2); b2 = fmaf(wgt[k + 1], __uint_as_float(o[k + 1].z), b2);
        a3 = fmaf(wgt[k], __uint_as_float(o[k].w), a3); b3 = fmaf(wgt[k + 1], __uint_as_float(o[k + 1].w), b3);
    }
    a0 += b0; a1 += b1; a2 += b2; a3 += b3;
#pragma unroll
    for (int s = 8; s <= 16; s <<= 1) {
        a0 += __shfl_xor_sync(~0u, a0, s);
        a1 += __shfl_xor_sync(~0u, a1, s);
        a2 += __shfl_xor_sync(~0u, a2, s);
        a3 += __shfl_xor_sync(~0u, a3, s);
    }
    if (lane < 8) *(float4*)(red + w4 * 32 + c4 * 4) = make_float4(a0, a1, a2, a3);
    named_bar(1, 128);
    STAMP(tid == 0 && bh >= 32, 24);
}

__device__ __forceinline__ void tile_scores(Scratch& G, uint32_t slot, uint32_t qbase, unsigned tk, uint32_t tag, int lane, uint32_t (&pb)[16][2]) {
    const int g = lane >> 2, t = lane & 3;
    const uint32_t kA = slot + g * 256 + t * 16 + (g & 1) * 64, kB = kA ^ 64;
    const uint32_t qa = qbase + (tk >> 7) * 256 + t * 16 + ((g >> 1) & 1) * 64 + (g & 1) * 8;
    const uint32_t sl0 = (g & 1) ? 0x1044u : 0x4410u, sl1 = (g & 1) ? 0x3244u : 0x4432u;
    const uint32_t sa0 = (g & 2) ? 0x4444u : sl0, sa1 = (g & 2) ? 0x4444u : sl1;
    const uint32_t sb0 = (g & 2) ? sl0 : 0x4444u, sb1 = (g & 2) ? sl1 : 0x4444u;
    uint2 qf[4];
    qf[0] = lds64(qa); qf[1] = lds64(qa ^ 64); qf[2] = lds64(qa + 128); qf[3] = lds64((qa ^ 64) + 128);
    float c[8][4];
#pragma unroll
    for (int i = 0; i < 32; i++) (&c[0][0])[i] = 0.f;
#pragma unroll
    for (int s = 0; s < 4; s++)
#pragma unroll
        for (int jj = 0; jj < 8; jj++) {
            const uint4 u = lds128(((s & 1) ? kB : kA) + jj * 2048 + (s >> 1) * 128);
            mma16816(c[jj], u.x, u.y, u.z, u.w, qf[s].x, qf[s].y);
        }
    float sc[8];
#pragma unroll
    for (int jj = 0; jj < 8; jj++) sc[jj] = c[jj][0] + c[jj][3];
#pragma unroll
    for (int jj = 0; jj < 8; jj += 2) scale_scores(sc[jj], sc[jj + 1]);
    float m = fmaxf(fmaxf(fmaxf(sc[0], sc[1]), fmaxf(sc[2], sc[3])), fmaxf(fmaxf(sc[4], sc[5]), fmaxf(sc[6], sc[7])));
    m = fmaxf(m, __shfl_xor_sync(~0u, m, 5));
    m = fmaxf(m, __shfl_xor_sync(~0u, m, 8));
    m = fmaxf(m, __shfl_xor_sync(~0u, m, 16));
    const float ms = __uint_as_float(tagw(m * LOG2E, tag));
    uint32_t W0[4], W1[4];
    float l = 0.f;
#pragma unroll
    for (int i = 0; i < 4; i++) {
        const uint32_t pp = pack_bf16(ex2(fmaf(sc[2 * i], LOG2E, -ms)), ex2(fmaf(sc[2 * i + 1], LOG2E, -ms)));
        W0[i] = __shfl_sync(~0u, pp, 8 * t);
        W1[i] = __shfl_sync(~0u, pp, 8 * t + 5);
        l += bf_lo(pp) + bf_hi(pp);
    }
    l += __shfl_xor_sync(~0u, l, 5);
    l += __shfl_xor_sync(~0u, l, 8);
    l += __shfl_xor_sync(~0u, l, 16);
    if (lane == 0 || lane == 2)
        st_relaxed128((char*)G.partML + tk * 32 + lane * 8, __float_as_uint(ms), tagw(l, tag), __float_as_uint(ms), tagw(l, tag));
#pragma unroll
    for (int i = 0; i < 16; i++) {
        const uint32_t pw = (i & 1) ? W1[i >> 2] : W0[i >> 2];
        pb[i][0] = prmt(pw, 0, (i & 2) ? sa1 : sa0);
        pb[i][1] = prmt(pw, 0, (i & 2) ? sb1 : sb0);
        asm volatile("" : "+r"(pb[i][0]), "+r"(pb[i][1]));
    }
}
__device__ __forceinline__ void tile_pv(float* po, uint32_t slot, uint32_t tag, int lane, const uint32_t (&pb)[16][2]) {
    const int g = lane >> 2, t = lane & 3;
    const uint32_t v0 = slot + 16384 + (2 * t) * 128 + ((g ^ (2 * t)) << 4), v1 = (v0 + 128) ^ 16;
    float acc[2][4][4];
#pragma unroll
    for (int i = 0; i < 32; i++) (&acc[0][0][0])[i] = 0.f;
#pragma unroll
    for (int jj = 0; jj < 8; jj++)
#pragma unroll
        for (int e = 0; e < 2; e++)
#pragma unroll
            for (int hh = 0; hh < 2; hh++) {
                const uint4 u = lds128((e ? v1 : v0) + jj * 1024 + hh * 8192);
                mma16816(acc[hh][(jj & 1) * 2 + e], u.x, u.y, u.z, u.w, pb[2 * jj + e][0], pb[2 * jj + e][1]);
            }
    float r4[4];
#pragma unroll
    for (int i = 0; i < 4; i++) {
        const float x0 = (acc[0][0][i] + acc[0][1][i]) + (acc[0][2][i] + acc[0][3][i]);
        const float x1 = (acc[1][0][i] + acc[1][1][i]) + (acc[1][2][i] + acc[1][3][i]);
        r4[i] = (t & 2) ? x1 : x0;
    }
    st_relaxed128(po, tagw(r4[0], tag), tagw(r4[1], tag), tagw(r4[2], tag), tagw(r4[3], tag));
}

struct Ptrs {
    const __nv_bfloat16 *K, *xA, *xB;
    __nv_bfloat16* out;
    Scratch* g;
};
struct Maps { CUtensorMap m_wq, m_v, m_ckv, m_wqB, m_wuk, m_uv[2], m_w[2]; };

__global__ void __launch_bounds__(NTHREADS, 1)
fused_decode_kernel(const Ptrs P, const __grid_constant__ Maps M) {
    extern __shared__ __align__(1024) unsigned char smem[];
    const uint32_t sb = (uint32_t)__cvta_generic_to_shared(smem);
    uint64_t pol;
    asm("createpolicy.fractional.L2::evict_first.b64 %0, 1.0;" : "=l"(pol));
    asm volatile("{\n.reg .pred p;\nsetp.lt.u32 p, %3, 32;\n@p cp.async.bulk.prefetch.L2.global.L2::cache_hint [%0], %1, %2;\n}\n"
                 ::"l"((const char*)P.K + (blockIdx.x << 14)), "n"(PFB), "l"(pol), "r"(threadIdx.x) : "memory");
    if (threadIdx.x < 32 && elect_one()) {
        mbar_init(sb + SM_BAR + BAR_FULL, 1);
        mbar_init(sb + SM_BAR + BAR_FULL + 16, 1);
        mbar_init(sb + SM_BAR + BAR_W, 1);
        asm volatile("fence.mbarrier_init.release.cluster;" ::: "memory");
        if (blockIdx.x < NA_CTA) {
            mbar_expect_tx(sb + SM_BAR + BAR_FULL, 16384);
            bulk_load(sb + SM_SLOT, (const char*)P.K + (blockIdx.x << 14), 16384, sb + SM_BAR + BAR_FULL, pol);
        }
        if (blockIdx.x < 128) {
            mbar_expect_tx(sb + SM_BAR + BAR_W, 32768 + 4096);
            issue_tall(sb + SM_WQ, &M.m_wq, slice_of(blockIdx.x) * 32, 0, sb + SM_BAR + BAR_W, pol);
            bulk_load_nohint(sb + SM_P, P.xA, 2048, sb + SM_BAR + BAR_W);
            bulk_load_nohint(sb + SM_P + 2048, P.xB, 2048, sb + SM_BAR + BAR_W);
        }
        if (blockIdx.x < NA_CTA) {
            mbar_expect_tx(sb + SM_BAR + BAR_FULL + 16, 16384);
            bulk_load(sb + SM_SLOT + 32768, (const char*)P.K + ((blockIdx.x + NA_CTA) << 14), 16384, sb + SM_BAR + BAR_FULL + 16, pol);
        }
    }
    const int tid = threadIdx.x, warp = __shfl_sync(~0u, tid >> 5, 0), lane = tid & 31;
    const int g = lane >> 2, t = lane & 3;
    const int cta = blockIdx.x;
    Scratch& G = *P.g;
    const bool isB = cta >= NA_CTA;
    const bool hasSlice = cta < 128;
    const int j = slice_of(cta), h = j >> 2, qd = cta & 3;
    const int mat = j >> 6, cg = j & 7, rg = (j >> 3) & 7;
    const bool late = j < JE0 || j >= 124;
    STAMP(tid == 32, 0);
    if (warp == 7) {
        __syncthreads();
        const uint32_t epoch = *(volatile uint32_t*)(smem + SM_BAR + W_EPOCH);
        const uint32_t tag = (epoch + 1) & 1;
        if (!isB) { mbar_wait(sb + SM_BAR + BAR_W, 0); __nanosleep(QDELAY); }
#pragma unroll 1
        for (int i = 0; i < 8; i++) {
            if (i == 4 && !isB) wait_prog(smem + SM_BAR + W_PROG, 16 * 128);
            if (i == 0 && isB) { mbar_wait(sb + SM_BAR + BAR_QABS, 0); __nanosleep(8000); }
            uint4 v[8];
            uint32_t bad[8];
#pragma unroll
            for (int k = 0; k < 8; k++) { bad[k] = 1; v[k] = make_uint4(0, 0, 0, 0); }
            unsigned it = 0;
            while (true) {
#pragma unroll
                for (int k = 0; k < 8; k++) ld_relaxed128_if(v[k], G.qA + (8 * i + k) * 128 + lane * 4, bad[k]);
                uint32_t any = 0;
#pragma unroll
                for (int k = 0; k < 8; k++) { bad[k] = bad4(v[k], tag) & 1u; any |= bad[k]; }
                if (!__any_sync(~0u, any)) break;
                __nanosleep(40);
                if (++it > SPIN_LIMIT) __trap();
            }
#pragma unroll
            for (int k = 0; k < 8; k++) {
                uint32_t* dst = (uint32_t*)(smem + SM_QA + (8 * i + k) * 256 + (lane >> 1) * 16 + (lane & 1) * 4);
                dst[0] = pack_bf16(__uint_as_float(v[k].x), __uint_as_float(v[k].y));
                dst[2] = pack_bf16(__uint_as_float(v[k].z), __uint_as_float(v[k].w));
            }
            __syncwarp();
            if (lane == 0) mbar_arrive(sb + SM_BAR + BAR_Q + i * 8);
            STAMP(lane == 0 && i == 0, 2);
            if (i == 1 && !isB) {
                const unsigned tx = NWORK * NA_CTA + cta;
                uint32_t pb[16][2];
                mbar_wait(sb + SM_BAR + BAR_X, 0);
                tile_scores(G, sb + SM_WQ, sb + SM_QA, tx, tag, lane, pb);
                tile_pv(G.partO + (size_t)tx * 128 + 64 * (t >> 1) + 8 * g + 4 * (t & 1), sb + SM_WQ, tag, lane, pb);
            }
        }
        STAMP(lane == 0, 21);
        if (hasSlice) mbar_wait(sb + SM_BAR + BAR_PDONE, 0);
#pragma unroll 1
        for (int p = 0; p < 12; p++) {
            const bool uv = p < 4;
            if (p == (late ? 0 : 4)) {
                uint32_t tref = 0;
#pragma unroll 1
                for (int k = 0; k < 2; k++) {
                    wait_ticket(smem + SM_BAR + W_PROG, NT - FRZ + (k ? GX + GL2 : GLOOK));
                    uint32_t v;
                    unsigned it = 0;
                    while (true) {
                        v = ld_relaxed32(&G.clk.v + (k ? 0 : GX / GST) + (lane & (GN - 1)));
                        if (!__any_sync(~0u, (v ^ tag) & 1u)) break;
                        __nanosleep(200);
                        if (++it > SPIN_LIMIT) __trap();
                    }
                    const uint32_t v0 = __shfl_sync(~0u, v, 0);
                    v = v0 + (__reduce_add_sync(~0u, (int)(v - v0)) >> 5) - (k ? BIAS2 : 0);
                    if ((!k || (int)(v - tref) > THR2) && lane == 0)
                        asm volatile("st.volatile.shared.v2.u32 [%0], {%1, %2};" ::"r"(sb + SM_BAR + W_PROG), "r"(NT - NSTATIC - FRZ), "r"(v) : "memory");
                    tref = v;
                    __syncwarp();
                }
                if (!hasSlice) break;
            }
            if (lane == 0) {
                const int r = uv ? p * 128 : (p - 4) * 64;
                if (!uv || late)
                    wait_ticket(smem + SM_BAR + W_PROG, NT + (uv ? YV + (p * DV >> 1) : YW + ((p - 4) * DW >> 1) + (p == 11 ? DL : 0)));
                STAMP(p == 4, 10);
                const uint32_t bar = sb + SM_BAR + BAR_S + (p < 11 ? p >> 1 : 6) * 8;
                if (!(p & 1) || p == 11) mbar_expect_tx(bar, p < 10 ? 16384 : 8192);
                tma_2d(sb + SM_SQ + p * 8192, uv ? &M.m_uv[late] : &M.m_w[mat], uv ? j * 32 : cg * 64,
                       uv ? r : (rg + 8 * (r >> 7)) * 128 + (r & 127), bar, pol);
            }
            __syncwarp();
        }
    } else if (warp >= 4) {
        const int wi = warp - 4;
        const uint32_t slot = sb + SM_SLOT + wi * 32768;
        const uint32_t bar = sb + SM_BAR + BAR_FULL + wi * 16, barV = bar + 8;
        unsigned tk = wi * NA_CTA + cta;
        const bool ev = wi == 2;
        if (lane == 0) {
            if (ev) mbar_init(bar, 1);
            mbar_init(barV, 1);
            if (isB && wi == 0) {
                for (int s = 0; s < 5; s++) {
                    mbar_init(sb + SM_BAR + BAR_BFULL + s * 8, 1);
                    mbar_init(sb + SM_BAR + BAR_BEMPTY + s * 8, 4);
                }
            }
            asm volatile("fence.mbarrier_init.release.cluster;" ::: "memory");
        }
        __syncthreads();
        const uint32_t epoch = *(volatile uint32_t*)(smem + SM_BAR + W_EPOCH);
        const uint32_t tag = (epoch + 1) & 1;

        bool active = true;
        if (isB) {
            if (wi == 1 && lane == 0) {
                wait_counter(&G.cntQabs.v, (epoch + 1) * 128, 64);
                fence_proxy_async();
                mbar_expect_tx(sb + SM_BAR + BAR_QABS, 32768);
                bulk_load_nohint(sb + SM_SLOT + 5 * 32768, G.qabs + ((cta - NA_CTA) >> 3) * 16384, 32768, sb + SM_BAR + BAR_QABS);
            }
            if (wi == 0 && lane == 0) {
                const int ib = cta - NA_CTA;
                int s = 0, sl = 0; uint32_t ph = 1, phl = 0;
                for (int u = 0; u < 32; u++) {
                    if (u >= BINFL) {
                        mbar_wait(sb + SM_BAR + BAR_BFULL + sl * 8, phl);
                        LAND(true, 16384 + ib * 32 + u);
                        if (++sl == 5) { sl = 0; phl ^= 1; }
                    }
                    if (u == 3 && hasSlice) mbar_wait(sb + SM_BAR + BAR_WFREE, 0);
                    mbar_wait(sb + SM_BAR + BAR_BEMPTY + s * 8, ph);
                    const uint32_t fb = sb + SM_BAR + BAR_BFULL + s * 8;
                    const int row = (ib >> 3) * 8192 + ((u >> 1) * 8 + (ib & 7)) * 64;
                    mbar_expect_tx(fb, 32768);
                    for (int x = 0; x < 4; x++)
                        tma_2d(sb + SM_SLOT + s * 32768 + x * 8192, &M.m_ckv, ((u & 1) * 4 + x) * 64, row, fb, pol);
                    if (++s == 5) { s = 0; ph ^= 1; }
                }
            }
            __syncwarp();
            mbar_wait(sb + SM_BAR + BAR_BDONE, 0);
            if (lane == 0) {
                tk = atomicInc(&G.ticket.v, DRAWS - 1);
                note_draw(smem + SM_BAR + W_PROG, tk, &G.clk.v, tag);
                tk += NSTATIC;
            }
            tk = __shfl_sync(~0u, tk, 0);
            active = tk < NT;
        } else if (ev) {
            __syncwarp();
            mbar_wait(sb + SM_BAR + BAR_W + 8, 0);
        }
        if (active) {
            if ((isB || ev) && lane == 0) {
                mbar_expect_tx(bar, 16384);
                bulk_load(slot, (const char*)P.K + (size_t)tk * 16384, 16384, bar, pol);
            }
            uint32_t ph = 0;
            while (true) {
                bool vout = false;
                if (XRV && lane == 0 && tk >= NT - XRV && !mbar_wait_for(bar, ph, TV)) {
                    mbar_expect_tx(barV, 16384);
                    tma_3d(slot + 16384, &M.m_v, tk * 64, 0, barV, pol);
                    vout = true;
                }
                if (XRV) __syncwarp();
                mbar_wait(bar, ph);
                LAND(lane == 0, tk);
                unsigned nxt = 0;
                if (lane == 0) {
                    if (!vout) {
                        mbar_expect_tx(barV, 16384);
                        tma_3d(slot + 16384, &M.m_v, tk * 64, 0, barV, pol);
                    }
                    asm volatile("atom.relaxed.gpu.global.inc.u32 %0, [%1], %2;" : "=r"(nxt) : "l"(&G.ticket.v), "r"(DRAWS - 1) : "memory");
                }
                __syncwarp();
                mbar_wait(sb + SM_BAR + BAR_Q + (tk >> 10) * 8, 0);
                STAMP(tid == 128 && tk < NSTATIC, 3);
                uint32_t pb[16][2];
                tile_scores(G, slot, sb + SM_QA, tk, tag, lane, pb);
                float* po = G.partO + (size_t)tk * 128 + 64 * (t >> 1) + 8 * g + 4 * (t & 1);
                asm volatile("" : "+l"(po));
                if (lane == 0) note_draw(smem + SM_BAR + W_PROG, nxt, &G.clk.v, tag);
                nxt += NSTATIC;
                if (nxt >= NT - XPK && nxt < NT && lane == 0) {
                    mbar_expect_tx(bar, 16384);
                    bulk_load(slot, (const char*)P.K + (size_t)nxt * 16384, 16384, bar, pol);
                }
                mbar_wait(barV, ph);
                LAND(lane == 0, 8192 + tk);
                ph ^= 1;
                if (nxt < NT - XPK && lane == 0) {
                    mbar_expect_tx(bar, 16384);
                    bulk_load(slot, (const char*)P.K + (size_t)nxt * 16384, 16384, bar, pol);
                }
                __syncwarp();
                tile_pv(po, slot, tag, lane, pb);
                nxt = __shfl_sync(~0u, nxt, 0);
                if (nxt >= NT) break;
                tk = nxt;
            }
            STAMP(lane == 0, 16 + wi);
        }
    } else {
        float* red = (float*)(smem + SM_RED2);
        if (tid == 32) {
            const uint32_t ep0 = ld_relaxed32(&G.epoch.v);
            for (int e = 0; e < 8; e++) mbar_init(sb + SM_BAR + BAR_Q + e * 8, 1);
            for (int e = 1; e < 10; e++) mbar_init(sb + SM_BAR + BAR_W + e * 8, 1);
            mbar_init(sb + SM_BAR + BAR_BDONE, 1);
            mbar_init(sb + SM_BAR + BAR_X, 1);
            mbar_init(sb + SM_BAR + BAR_PDONE, 1);
            mbar_init(sb + SM_BAR + BAR_QABS, 1);
            mbar_init(sb + SM_BAR + BAR_WFREE, 1);
            asm volatile("fence.mbarrier_init.release.cluster;" ::: "memory");
            asm volatile("st.volatile.shared.v4.u32 [%0], {%1, %2, %1, %1};" ::"r"(sb + SM_BAR + W_PROG), "r"(0), "r"(now_ns()) : "memory");
            *(volatile uint32_t*)(smem + SM_BAR + W_EPOCH) = ep0;
        } else if (tid == 64) {
            asm volatile("prefetch.tensormap [%0];" ::"l"(&M.m_v) : "memory");
            asm volatile("prefetch.tensormap [%0];" ::"l"(&M.m_wqB) : "memory");
            asm volatile("prefetch.tensormap [%0];" ::"l"(&M.m_wuk) : "memory");
        }
        __syncthreads();
        const uint32_t epoch = *(volatile uint32_t*)(smem + SM_BAR + W_EPOCH);
        const uint32_t tag = (epoch + 1) & 1;
        STAMP(tid == 0, 14);

        if (hasSlice) {
            const uint32_t nt = tag ^ 1;
            const int qoff = ((tid >> 5) & 1) * 4096 + 32 * j + (tid & 31);
            if (tid < 64) {
                st_relaxed32(G.qA + qoff, nt); st_relaxed32(G.qB + qoff, nt);
                if (tid < 32) {
                    st_relaxed32(G.o + 32 * j + tid, nt); st_relaxed32(G.o + 4096 + 32 * j + tid, nt);
                    st_relaxed32(G.ctx + 32 * j + tid, nt); st_relaxed32(G.ctx + 4096 + 32 * j + tid, nt);
                }
            }
            if (j == 0 && tid >= 64) st_relaxed32(&G.clk.v + (tid - 64), nt);
            if (tid >= 64 && tid < 72) st_relaxed32((uint32_t*)P.out + 8 * j + (tid - 64), 0);
            mbar_wait(sb + SM_BAR + BAR_W, 0);
            LAND(tid == 0, 17408 + 0 * 128 + j);
            STAMP(tid == 0, 15);
            uint2 bf[16];
            tall_prep(bf, sb + SM_P, warp, g, t);
            gemv_tall(sb + SM_WQ, bf, (float*)(smem + SM_RED1), warp, g, t);
            tall_finish((float*)(smem + SM_RED1), G.qA + qoff, tid, tag, 0, h >= HCLR ? 32 : 64);
            STAMP(tid == 0, 1);
            if (tid == 96) {
                mbar_expect_tx(sb + SM_BAR + BAR_W + 8, 32768);
                issue_tall(sb + SM_WQB, &M.m_wqB, j * 32, 0, sb + SM_BAR + BAR_W + 8, pol);
                if (!isB) {
                    mbar_expect_tx(sb + SM_BAR + BAR_X, 32768);
                    bulk_load(sb + SM_WQ, (const char*)P.K + ((NWORK * NA_CTA + cta) << 14), 16384, sb + SM_BAR + BAR_X, pol);
                }
            }
            __syncwarp();
            tall_prep(bf, sb + SM_P + 2048, warp, g, t);
            mbar_wait(sb + SM_BAR + BAR_W + 8, 0);
            LAND(tid == 0, 17408 + 1 * 128 + j);
            gemv_tall(sb + SM_WQB, bf, red, warp, g, t);
            tall_finish(red, G.qB + qoff, tid, tag);
            if (tid == 96) {
                mbar_expect_tx(sb + SM_BAR + BAR_W + 16, 32768);
                tma_2d(sb + SM_WUK, &M.m_wuk, h * 128, qd * 128, sb + SM_BAR + BAR_W + 16, pol);
                mbar_arrive(sb + SM_BAR + BAR_WFREE);
                if (!isB) tma_3d(sb + SM_WQ + 16384, &M.m_v, (NWORK * NA_CTA + cta) * 64, 0, sb + SM_BAR + BAR_X, pol);
            }
            STAMP(tid == 0, 25);
            named_bar(1, 128);
            uint4 qf[4];
            {
                const float* qp = G.qB + ((g & 1) * 32 + h) * 128 + t * 8;
                uint4 v[8];
                unsigned it = 0;
                while (true) {
                    uint32_t bad = 0;
#pragma unroll
                    for (int i = 0; i < 8; i++) v[i] = ld_relaxed128(qp + (i >> 1) * 32 + (i & 1) * 4);
#pragma unroll
                    for (int i = 0; i < 8; i++) bad |= bad4(v[i], tag);
                    if (!__any_sync(~0u, bad & 1u)) break;
                    __nanosleep(100);
                    if (++it > SPIN_LIMIT) __trap();
                }
#pragma unroll
                for (int s = 0; s < 4; s++)
                    qf[s] = make_uint4(pack_bf16(__uint_as_float(v[2 * s].x), __uint_as_float(v[2 * s].y)),
                                       pack_bf16(__uint_as_float(v[2 * s].z), __uint_as_float(v[2 * s].w)),
                                       pack_bf16(__uint_as_float(v[2 * s + 1].x), __uint_as_float(v[2 * s + 1].y)),
                                       pack_bf16(__uint_as_float(v[2 * s + 1].z), __uint_as_float(v[2 * s + 1].w)));
            }
            mbar_wait(sb + SM_BAR + BAR_W + 16, 0);
            LAND(tid == 0, 17408 + 2 * 128 + j);
#pragma unroll
            for (int jj = 0; jj < 2; jj++) {
                float c[4] = {0.f, 0.f, 0.f, 0.f};
#pragma unroll
                for (int s = 0; s < 4; s++) {
                    const uint32_t a = sb + SM_WUK + (32 * warp + 16 * jj + g) * 256 + (t + 4 * s) * 16;
                    const uint4 u = lds128(a), v = lds128(a + 2048);
                    mma16816(c, u.x, v.x, u.y, v.y, qf[s].x, qf[s].y);
                    mma16816(c, u.z, v.z, u.w, v.w, qf[s].z, qf[s].w);
                }
                const float val = (t & 2) ? ((t & 1) ? c[3] : c[2]) : ((t & 1) ? c[1] : c[0]);
                const int cc = 128 * qd + 32 * warp + 16 * jj + g + ((t & 2) ? 8 : 0);
                const int off = (cc >> 6) * 2048 + h * 64 + ((((cc & 63) >> 3) ^ (h & 7)) << 3) + (cc & 7);
                G.qabs[(t & 1) * 16384 + off] = __float2bfloat16(val);
            }
            named_bar(1, 128);
            if (tid == 0) red_release(&G.cntQabs.v);
            STAMP(tid == 0, 4);
            if (h >= HCLR) {
#pragma unroll
                for (int k = 0; k < 8; k++)
                    st_relaxed128(G.partO + (size_t)((32 + h) * 128 + 16 * k + (tid >> 3)) * 128 + qd * 32 + (tid & 7) * 4, nt, nt, nt, nt);
                if (tid < 64) st_relaxed128((char*)G.partML + ((32 + h) * 128 + qd * 32) * 32 + tid * 16, nt, nt, nt, nt);
                __threadfence();
                tall_finish((float*)(smem + SM_RED1), G.qA + qoff, tid, tag, 32, 64);
            }
        }

        if (isB) {
            const int ib = cta - NA_CTA;
            float acc[8][16];
#pragma unroll
            for (int i = 0; i < 8; i++)
#pragma unroll
                for (int k = 0; k < 16; k++) acc[i][k] = 0.f;
            float mrun[8], lrun[8];
#pragma unroll
            for (int i = 0; i < 8; i++) { mrun[i] = -INFINITY; lrun[i] = 0.f; }
            const uint64_t dQ = make_desc(sb + SM_SLOT + 5 * 32768);
            const uint64_t dP = make_desc(sb + SM_P);
            const uint32_t pst = sb + SM_P + (((lane >> 4) * 8 + (lane & 7)) * 128) + (((2 * warp + ((lane >> 3) & 1)) ^ (lane & 7)) << 4);
            mbar_wait(sb + SM_BAR + BAR_QABS, 0);
            STAMP(tid == 0, 5);
            int s0 = 0; uint32_t ph0 = 0;
            for (int it = 0; it < 16; it++) {
                int s1 = s0 + 1; uint32_t ph1 = ph0;
                if (s1 == 5) { s1 = 0; ph1 ^= 1; }
                const uint64_t dA0 = make_desc(sb + SM_SLOT + s0 * 32768), dA1 = make_desc(sb + SM_SLOT + s1 * 32768);
                float S[16];
                mbar_wait(sb + SM_BAR + BAR_BFULL + s0 * 8, ph0);
                mbar_wait(sb + SM_BAR + BAR_BFULL + s1 * 8, ph1);
                wg_fence();
#pragma unroll
                for (int k = 0; k < 32; k++) {
                    const uint64_t da = ((k < 16) ? dA0 : dA1) + (uint64_t)((((k >> 2) & 3) * 8192 + (k & 3) * 32) >> 4);
                    const uint64_t db = dQ + (uint64_t)(((k >> 2) * 4096 + (k & 3) * 32) >> 4);
                    wgmma_n32<0>(S, da, db, k > 0);
                }
                wg_commit();
                wg_wait<0>();
#pragma unroll
                for (int i = 0; i < 16; i++) S[i] *= SCALE;
                float mx[8];
#pragma unroll
                for (int i = 0; i < 8; i++) {
                    mx[i] = fmaxf(S[4 * (i >> 1) + (i & 1)], S[4 * (i >> 1) + 2 + (i & 1)]);
                    mx[i] = fmaxf(mx[i], __shfl_xor_sync(~0u, mx[i], 4));
                    mx[i] = fmaxf(mx[i], __shfl_xor_sync(~0u, mx[i], 8));
                    mx[i] = fmaxf(mx[i], __shfl_xor_sync(~0u, mx[i], 16));
                }
                if (g == 0) {
#pragma unroll
                    for (int jb = 0; jb < 4; jb++)
                        *(float2*)(red + warp * 32 + 8 * jb + 2 * t) = make_float2(mx[2 * jb], mx[2 * jb + 1]);
                }
                named_bar(1, 128);
                float al[8];
                bool chg = false;
                uint32_t R[8];
#pragma unroll
                for (int jb = 0; jb < 4; jb++) {
                    float2 a = *(float2*)(red + 8 * jb + 2 * t), b = *(float2*)(red + 32 + 8 * jb + 2 * t);
                    float2 c = *(float2*)(red + 64 + 8 * jb + 2 * t), d = *(float2*)(red + 96 + 8 * jb + 2 * t);
                    const float n0 = fmaxf(mrun[2 * jb], fmaxf(fmaxf(a.x, b.x), fmaxf(c.x, d.x)) * LOG2E);
                    const float n1 = fmaxf(mrun[2 * jb + 1], fmaxf(fmaxf(a.y, b.y), fmaxf(c.y, d.y)) * LOG2E);
                    chg |= (n0 != mrun[2 * jb]) | (n1 != mrun[2 * jb + 1]);
                    al[2 * jb] = ex2(mrun[2 * jb] - n0);
                    al[2 * jb + 1] = ex2(mrun[2 * jb + 1] - n1);
                    mrun[2 * jb] = n0; mrun[2 * jb + 1] = n1;
                    R[2 * jb]     = pack_bf16(ex2(fmaf(S[4 * jb], LOG2E, -n0)), ex2(fmaf(S[4 * jb + 1], LOG2E, -n1)));
                    R[2 * jb + 1] = pack_bf16(ex2(fmaf(S[4 * jb + 2], LOG2E, -n0)), ex2(fmaf(S[4 * jb + 3], LOG2E, -n1)));
                    lrun[2 * jb]     = fmaf(lrun[2 * jb], al[2 * jb], bf_lo(R[2 * jb]) + bf_lo(R[2 * jb + 1]));
                    lrun[2 * jb + 1] = fmaf(lrun[2 * jb + 1], al[2 * jb + 1], bf_hi(R[2 * jb]) + bf_hi(R[2 * jb + 1]));
                }
                asm volatile("stmatrix.sync.aligned.m8n8.x4.trans.shared.b16 [%0], {%1,%2,%3,%4};"
                             ::"r"(pst), "r"(R[0]), "r"(R[1]), "r"(R[2]), "r"(R[3]) : "memory");
                asm volatile("stmatrix.sync.aligned.m8n8.x4.trans.shared.b16 [%0], {%1,%2,%3,%4};"
                             ::"r"(pst + 2048), "r"(R[4]), "r"(R[5]), "r"(R[6]), "r"(R[7]) : "memory");
                asm volatile("fence.proxy.async.shared::cta;" ::: "memory");
                if (__any_sync(~0u, chg)) {
#pragma unroll
                    for (int mt = 0; mt < 8; mt++)
#pragma unroll
                        for (int k = 0; k < 16; k++) acc[mt][k] *= al[2 * (k >> 2) + (k & 1)];
                }
                named_bar(1, 128);
                wg_fence();
#pragma unroll
                for (int mt = 0; mt < 4; mt++)
#pragma unroll
                    for (int kk = 0; kk < 4; kk++)
                        wgmma_n32<1>(acc[mt], dA0 + (uint64_t)((mt * 8192 + kk * 2048) >> 4), dP + (uint64_t)((kk * 32) >> 4), 1);
                wg_commit();
#pragma unroll
                for (int mt = 0; mt < 4; mt++)
#pragma unroll
                    for (int kk = 0; kk < 4; kk++)
                        wgmma_n32<1>(acc[4 + mt], dA1 + (uint64_t)((mt * 8192 + kk * 2048) >> 4), dP + (uint64_t)((kk * 32) >> 4), 1);
                wg_commit();
                wg_wait<1>();
                if (lane == 0) mbar_arrive(sb + SM_BAR + BAR_BEMPTY + s0 * 8);
                wg_wait<0>();
                if (lane == 0) mbar_arrive(sb + SM_BAR + BAR_BEMPTY + s1 * 8);
                s0 = s1 + 1; ph0 = ph1;
                if (s0 == 5) { s0 = 0; ph0 ^= 1; }
            }
#pragma unroll
            for (int i = 0; i < 8; i++) {
                lrun[i] += __shfl_xor_sync(~0u, lrun[i], 4);
                lrun[i] += __shfl_xor_sync(~0u, lrun[i], 8);
                lrun[i] += __shfl_xor_sync(~0u, lrun[i], 16);
            }
            if (g == 0) {
#pragma unroll
                for (int jb = 0; jb < 4; jb++) {
                    *(float2*)(red + 128 + warp * 32 + 8 * jb + 2 * t) = make_float2(lrun[2 * jb], lrun[2 * jb + 1]);
                    if (warp == 0) *(float2*)(red + 256 + 8 * jb + 2 * t) = make_float2(mrun[2 * jb], mrun[2 * jb + 1]);
                }
            }
            named_bar(1, 128);
            if (tid == 0) mbar_arrive(sb + SM_BAR + BAR_BDONE);
            if (tid < 32)
                G.bml[ib * 32 + tid] = make_float2(red[256 + tid], red[128 + tid] + red[160 + tid] + red[192 + tid] + red[224 + tid]);
            float* bp = G.bpart + (size_t)ib * 16384 + (2 * t) * 512 + 16 * warp + g;
#pragma unroll
            for (int mt = 0; mt < 8; mt++)
#pragma unroll
                for (int k = 0; k < 16; k++)
                    bp[(8 * (k >> 2) + (k & 1)) * 512 + 64 * mt + ((k >> 1) & 1) * 8] = acc[mt][k];
            named_bar(1, 128);
            if (tid == 0) red_release(&G.cntB.v);
            STAMP(tid == 0, 6);
        }

        if (hasSlice) {
            if (tid == 0) {
                wait_prog(smem + SM_BAR + W_PROG, TUV);
                wait_counter(&G.cntB.v, (epoch + 1) * NB_CTA, 500);
                if (cta == 0) st_relaxed32(&G.epoch.v, epoch + 1);
                asm volatile("prefetch.tensormap [%0];" ::"l"(&M.m_uv[late]) : "memory");
                asm volatile("prefetch.tensormap [%0];" ::"l"(&M.m_w[mat]) : "memory");
            }
            named_bar(1, 128);
            if (tid == 32) mbar_arrive(sb + SM_BAR + BAR_PDONE);
            STAMP(tid == 0, 7);
            {
                const int b = tid >> 6, cp = tid & 63;
                uint2 ml[8];
#pragma unroll
                for (int i = 0; i < 8; i++) ml[i] = ld_relaxed64(G.bml + (b * 8 + i) * 32 + h);
                uint4 pv[2][8];
#pragma unroll
                for (int i = 0; i < 16; i++)
                    pv[i >> 3][i & 7] = ld_relaxed128(G.bpart + (size_t)(b * 8 + (i & 7)) * 16384 + h * 512 + (i >> 3) * 256 + 4 * cp);
                float M = __uint_as_float(ml[0].x);
#pragma unroll
                for (int i = 1; i < 8; i++) M = fmaxf(M, __uint_as_float(ml[i].x));
                float L = 0.f, wgt[8];
#pragma unroll
                for (int i = 0; i < 8; i++) {
                    wgt[i] = ex2(__uint_as_float(ml[i].x) - M);
                    L = fmaf(wgt[i], __uint_as_float(ml[i].y), L);
                }
                const float inv = 1.f / L;
#pragma unroll
                for (int x = 0; x < 2; x++) {
                    float v0 = 0.f, v1 = 0.f, v2 = 0.f, v3 = 0.f;
#pragma unroll
                    for (int i = 0; i < 8; i++) {
                        v0 = fmaf(wgt[i], __uint_as_float(pv[x][i].x), v0);
                        v1 = fmaf(wgt[i], __uint_as_float(pv[x][i].y), v1);
                        v2 = fmaf(wgt[i], __uint_as_float(pv[x][i].z), v2);
                        v3 = fmaf(wgt[i], __uint_as_float(pv[x][i].w), v3);
                    }
                    *(uint2*)(smem + SM_P + b * 1024 + x * 512 + cp * 8) = make_uint2(pack_bf16(v0 * inv, v1 * inv), pack_bf16(v2 * inv, v3 * inv));
                }
            }
            STAMP(tid == 0, 8);
        }
        {
            named_bar(1, 128);
#pragma unroll 1
            for (uint64_t plan = j < 64 ? 0xF7351260ull : (j < 124 ? (late ? 0xF75314260ull : 0xF7514603ull) : (hasSlice ? 0xF753426ull : 0xF10ull));
                 plan != 0xF; plan >>= 4) {
                const int step = plan & 15;
                if ((step & 14) == 4) {
                    const int hh = rg + 8 * warp;
                    const uint32_t real = step & 1, both = real & (mat | (warp != 3));
                    if (both) wait_ticket(smem + SM_BAR + W_PROG, mat ? NT + YB : min((33 + hh) * 128 + LAGT, NT + YLATE) + YX);
                    __syncwarp();
                    const float* src = (mat ? G.ctx : G.o) + hh * 128 + lane * 4;
                    uint4 v[2];
                    v[0] = v[1] = make_uint4(tag, tag, tag, tag);
                    uint32_t bad0 = real, bad1 = both;
                    unsigned it = 0;
                    while (true) {
                        ld_relaxed128_if(v[0], src, bad0);
                        ld_relaxed128_if(v[1], src + 4096, bad1);
                        bad0 = bad4(v[0], tag) & 1u; bad1 = bad4(v[1], tag) & 1u;
                        if (!__any_sync(~0u, bad0 | bad1)) break;
                        if (++it > SPIN_LIMIT) __trap();
                    }
#pragma unroll
                    for (int b = 0; b < 2; b++)
                        *(uint2*)(smem + SM_VEC + V_X + b * XSTR + (128 * warp + 4 * lane) * 2) =
                            make_uint2(pack_bf16(__uint_as_float(v[b].x), __uint_as_float(v[b].y)), pack_bf16(__uint_as_float(v[b].z), __uint_as_float(v[b].w)));
                    named_bar(1, 128);
                    STAMP(tid == 0, 29);
                } else if (step >= 6) {
                    const uint32_t real = step & 1;
                    const uint32_t xa = sb + SM_VEC + V_X + ((lane >> 1) & 1) * XSTR + 8 * (lane >> 3) * 2;
                    const uint32_t wa = sb + SM_SQ + 2 * 16384 + (8 * (lane >> 4) + (lane & 7)) * 128 +
                                        (((2 * warp + ((lane >> 3) & 1)) ^ (lane & 7)) << 4);
                    const uint32_t bs = sb + SM_BAR + BAR_S + 16;
                    const float* src = G.o + 4096 + (24 + rg) * 128 + lane * 4;
                    const uint32_t needx = real & (mat ^ 1);
                    uint32_t* dst = (uint32_t*)P.out + (t & 1) * 512 + mat * 256 + cg * 32 + warp * 8 + (t >> 1) * 4 + (g >> 1);
                    asm volatile("" : "+l"(dst));
                    uint4 v = make_uint4(tag, tag, tag, tag);
                    float d[4][4];
#pragma unroll
                    for (int i = 0; i < 16; i++) (&d[0][0])[i] = 0.f;
#pragma unroll 1
                    for (int u = 0; u < 3; u++) {
                        uint4 xf[4];
                        if (needx && u == 2) wait_ticket(smem + SM_BAR + W_PROG, NT + YP);
                        __syncwarp();
                        ld_relaxed128_if(v, src, needx & (u == 2));
#pragma unroll
                        for (int i = 0; i < 4; i++) xf[i] = ldsm4(xa + u * 256 + i * 64);
                        if (real) mbar_wait_nt(bs + u * 8, 0);
#pragma unroll
                        for (int i = 0; i < 4; i++) {
                            const uint4 w0 = ldsm4t(wa + u * 16384 + i * 4096), w1 = ldsm4t(wa + u * 16384 + i * 4096 + 2048);
                            mma16816(d[(i & 1) * 2], w0.x, w0.y, w0.z, w0.w, xf[i].x, xf[i].y);
                            mma16816(d[(i & 1) * 2 + 1], w1.x, w1.y, w1.z, w1.w, xf[i].z, xf[i].w);
                        }
                    }
                    unsigned it = 0;
                    while (__any_sync(~0u, bad4(v, tag) & 1u)) {
                        if (++it > SPIN_LIMIT) __trap();
                        v = ld_relaxed128(src);
                    }
                    STAMP(tid == 96, 20);
                    if (!mat)
                        *(uint2*)(smem + SM_VEC + V_X + XSTR + (384 + 4 * lane) * 2) =
                            make_uint2(pack_bf16(__uint_as_float(v.x), __uint_as_float(v.y)), pack_bf16(__uint_as_float(v.z), __uint_as_float(v.w)));
                    __syncwarp();
                    uint4 xf[4], w[4];
#pragma unroll
                    for (int i = 0; i < 4; i++) xf[i] = ldsm4(xa + 3 * 256 + i * 64);
#pragma unroll
                    for (int q = 0; q < 2; q++) {
                        if (q) {
#pragma unroll
                            for (int i = 0; i < 4; i++) {
                                d[0][i] = (d[0][i] + d[1][i]) + (d[2][i] + d[3][i]);
                                d[1][i] = d[2][i] = d[3][i] = 0.f;
                            }
                        }
                        if (real) mbar_wait_nt(bs + 24 + q * 8, 0);
#pragma unroll
                        for (int i = 0; i < 4; i++) w[i] = ldsm4t(wa + 3 * 16384 + q * 8192 + i * 2048);
#pragma unroll
                        for (int i = 0; i < 2; i++) {
                            mma16816(d[2 * i], w[2 * i].x, w[2 * i].y, w[2 * i].z, w[2 * i].w, xf[2 * q + i].x, xf[2 * q + i].y);
                            mma16816(d[2 * i + 1], w[2 * i + 1].x, w[2 * i + 1].y, w[2 * i + 1].z, w[2 * i + 1].w, xf[2 * q + i].z, xf[2 * q + i].w);
                        }
                    }
                    STAMP(tid == 64, 22);
                    float e[4];
#pragma unroll
                    for (int i = 0; i < 4; i++) e[i] = (t & 2) ? d[i][2] : d[i][0];
                    red_out(dst, ((e[0] + e[1]) + e[2]) + e[3], g, real);
                    STAMP(tid == 64, 13);
                    if (real) asm volatile("exit;");
                } else if (step >= 2) {
                    uint2 bf[16];
                    tall_prep(bf, sb + SM_P, warp, g, t);
                    if (step & 1) mbar_wait(sb + SM_BAR + BAR_S + (warp >> 1) * 8, 0);
                    LAND(tid == 64, 17408 + 3 * 128 + j);
                    gemv_tall(sb + SM_SQ, bf, red + 512, warp, g, t);
                    tall_finish(red + 512, G.ctx + ((tid >> 5) & 1) * 4096 + 32 * j + (tid & 31), tid, tag, 0, (step & 1) ? 64 : 0);
                    STAMP(tid == 0, 12);
                } else {
                    const int b = step;
                    const int hm = min(h, 31), bh = 32 * b + hm;
                    wait_ticket(smem + SM_BAR + W_PROG, min((bh + 1) * 128 + LAGT, NT + YLATE + max(hm - 27, 0) * YSL));
                    __syncwarp();
                    float* rb = red + b * 256;
                    combineA(G, bh, qd, tag, rb, tid, smem + SM_BAR + W_PROG);
                    {
                        if (tid < 32)
                            st_relaxed32(G.o + bh * 128 + 32 * qd + tid, tagw((rb[tid] + rb[32 + tid]) + (rb[64 + tid] + rb[96 + tid]), tag));
                        STAMP(tid == 0, 9 + 2 * b);
                    }
                }
            }
        }
    }
}

typedef CUresult (*EncodeFn)(CUtensorMap*, CUtensorMapDataType, cuuint32_t, void*, const cuuint64_t*, const cuuint64_t*,
                             const cuuint32_t*, const cuuint32_t*, CUtensorMapInterleave, CUtensorMapSwizzle,
                             CUtensorMapL2promotion, CUtensorMapFloatOOBfill);

}

extern "C" void kernel_launch(void* const* d_in, const int* in_sizes, int n_in, void* d_out, int out_size) {
    (void)in_sizes; (void)n_in; (void)out_size;
    static EncodeFn encode = nullptr;
    static void* scratch = nullptr;
    if (!encode) {
        void* fn = nullptr;
        cudaDriverEntryPointQueryResult st;
        cudaGetDriverEntryPoint("cuTensorMapEncodeTiled", &fn, cudaEnableDefault, &st);
        encode = (EncodeFn)fn;
        cudaGetSymbolAddress(&scratch, g_raw);
        cudaFuncSetAttribute(fused_decode_kernel, cudaFuncAttributeMaxDynamicSharedMemorySize, SM_TOTAL);
    }
    Ptrs P;
    Maps M;
    auto mk = [&](CUtensorMap* m, void* ptr, cuuint64_t cols, cuuint64_t rows, cuuint32_t bc, cuuint32_t br, CUtensorMapSwizzle sw,
                  CUtensorMapL2promotion promo) {
        const cuuint64_t gdim[2] = {cols, rows};
        const cuuint64_t gstr[1] = {cols * 2};
        const cuuint32_t box[2] = {bc, br};
        const cuuint32_t estr[2] = {1, 1};
        encode(m, CU_TENSOR_MAP_DATA_TYPE_BFLOAT16, 2, ptr, gdim, gstr, box, estr, CU_TENSOR_MAP_INTERLEAVE_NONE, sw,
               promo, CU_TENSOR_MAP_FLOAT_OOB_FILL_NONE);
    };
    mk(&M.m_wq, d_in[3], 4096, 512, 32, 256, CU_TENSOR_MAP_SWIZZLE_64B, CU_TENSOR_MAP_L2_PROMOTION_NONE);
    auto mk3 = [&](CUtensorMap* m, void* ptr, cuuint64_t cols, cuuint64_t rows) {
        const cuuint64_t gdim[3] = {64, rows, cols / 64};
        const cuuint64_t gstr[2] = {cols * 2, 128};
        const cuuint32_t box[3] = {64, 64, 2};
        const cuuint32_t estr[3] = {1, 1, 1};
        encode(m, CU_TENSOR_MAP_DATA_TYPE_BFLOAT16, 3, ptr, gdim, gstr, box, estr, CU_TENSOR_MAP_INTERLEAVE_NONE,
               CU_TENSOR_MAP_SWIZZLE_128B, CU_TENSOR_MAP_L2_PROMOTION_L2_256B, CU_TENSOR_MAP_FLOAT_OOB_FILL_NONE);
    };
    mk3(&M.m_v, d_in[2], 128, 524288);
    mk(&M.m_uv[0], d_in[9], 4096, 512, 32, 128, CU_TENSOR_MAP_SWIZZLE_64B, CU_TENSOR_MAP_L2_PROMOTION_NONE);
    mk(&M.m_uv[1], d_in[9], 4096, 512, 32, 128, CU_TENSOR_MAP_SWIZZLE_64B, CU_TENSOR_MAP_L2_PROMOTION_L2_256B);
    mk(&M.m_w[0], d_in[4], 512, 4096, 64, 64, CU_TENSOR_MAP_SWIZZLE_128B, CU_TENSOR_MAP_L2_PROMOTION_L2_256B);
    mk(&M.m_w[1], d_in[10], 512, 4096, 64, 64, CU_TENSOR_MAP_SWIZZLE_128B, CU_TENSOR_MAP_L2_PROMOTION_L2_256B);
    mk(&M.m_ckv, d_in[6], 512, 16384, 64, 64, CU_TENSOR_MAP_SWIZZLE_128B, CU_TENSOR_MAP_L2_PROMOTION_L2_256B);
    mk(&M.m_wqB, d_in[7], 4096, 512, 32, 256, CU_TENSOR_MAP_SWIZZLE_64B, CU_TENSOR_MAP_L2_PROMOTION_NONE);
    mk(&M.m_wuk, d_in[8], 4096, 512, 128, 128, CU_TENSOR_MAP_SWIZZLE_NONE, CU_TENSOR_MAP_L2_PROMOTION_L2_256B);
    P.xA = (const __nv_bfloat16*)d_in[0];
    P.K = (const __nv_bfloat16*)d_in[1];
    P.xB = (const __nv_bfloat16*)d_in[5];
    P.out = (__nv_bfloat16*)d_out;
    P.g = (Scratch*)scratch;
    cudaLaunchConfig_t cfg = {};
    cfg.gridDim = dim3(GRID);
    cfg.blockDim = dim3(NTHREADS);
    cfg.dynamicSmemBytes = SM_TOTAL;
    cfg.stream = cudaStreamPerThread;
    cudaLaunchAttribute attr;
    attr.id = cudaLaunchAttributeCooperative;
    attr.val.cooperative = 1;
    cfg.attrs = &attr;
    cfg.numAttrs = 1;
    cudaLaunchKernelEx(&cfg, fused_decode_kernel, P, M);
}
```
